```python
import torch

def _softmax(x, axis=-1):
    return torch.softmax(x, dim=axis)
def _gelu(x):
    return torch.nn.functional.gelu(x, approximate="tanh")
def _silu(x):
    return torch.nn.functional.silu(x)
def _sigmoid(x):
    return torch.sigmoid(x)
def _layernorm(x, axis=-1, eps=1e-5):
    m = x.mean(dim=axis, keepdim=True)
    v = x.var(dim=axis, keepdim=True, unbiased=False)
    return (x - m) / torch.sqrt(v + eps)
def _scatter_add(tgt, idx, src, axis=0):
    return tgt.clone().index_add_(axis, idx, src)
def _segment_sum(src, seg, n):
    out = torch.zeros((n,) + src.shape[1:], dtype=src.dtype)
    return out.index_add_(0, seg, src)
def _pad(x, pw):
    flat = tuple(v for pair in reversed(pw) for v in pair)
    return torch.nn.functional.pad(x, flat)

kernel_name = 'recurrent_scan__ssm_conv_s5__mixer_s_mlp__prompt'

def setup_inputs():

    _w = (lambda a: (lambda t: t.to(torch.bfloat16) if t.is_floating_point() else t)(torch.as_tensor(a)))
    def _A_setup():
        B, S, D = 1, 2048, 512
        P = D
        Lambda_re = -0.5 * (lambda _x: torch.exp(torch.as_tensor(_x)))((lambda *s: torch.randn(*s, dtype=torch.bfloat16) * 0.2)(P))
        Lambda_im = (lambda *s: torch.randn(*s, dtype=torch.bfloat16) * 0.4)(P) * 1.0
        B_re = (lambda *s: torch.randn(*s, dtype=torch.bfloat16) * 0.2)(P, D) * (D ** -0.5)
        B_im = (lambda *s: torch.randn(*s, dtype=torch.bfloat16) * 0.2)(P, D) * (D ** -0.5)
        C_re = (lambda *s: torch.randn(*s, dtype=torch.bfloat16) * 0.2)(D, P) * (P ** -0.5)
        C_im = (lambda *s: torch.randn(*s, dtype=torch.bfloat16) * 0.2)(D, P) * (P ** -0.5)
        log_dt = (lambda *s: torch.randn(*s, dtype=torch.bfloat16) * 0.2)(P) * 0.3 - 2.0
        Dskip = (lambda *s: torch.randn(*s, dtype=torch.bfloat16) * 0.05)(D)
        return {
            "x": _w((lambda *s: torch.randn(*s, dtype=torch.bfloat16) * 0.05)(B, S, D)),
            "Lambda_re": _w(Lambda_re),
            "Lambda_im": _w(Lambda_im),
            "B_re": _w(B_re),
            "B_im": _w(B_im),
            "C_re": _w(C_re),
            "C_im": _w(C_im),
            "log_dt": _w(log_dt),
            "Dskip": _w(Dskip),
        }
    _A_in = _A_setup()

    def _B_setup():
        B, S, D, F = 1, 2048, 512, 1792
        return {
            "x":  _w((lambda *s: torch.randn(*s, dtype=torch.bfloat16) * 0.05)(B, S, D)),
            "w1": _w((lambda *s: torch.randn(*s, dtype=torch.bfloat16) * 3.2)(D, D) * (D ** -0.5)),
            "w2": _w((lambda *s: torch.randn(*s, dtype=torch.bfloat16) * 3.2)(D, D) * (D ** -0.5)),
            "w3": _w((lambda *s: torch.randn(*s, dtype=torch.bfloat16) * 3.2)(D, F) * (D ** -0.5)),
            "w4": _w((lambda *s: torch.randn(*s, dtype=torch.bfloat16) * 3.2)(F, D) * (F ** -0.5)),
        }
    _B_in = _B_setup()

    return {
        "A_x": _A_in["x"],
        "A_Lambda_re": _A_in["Lambda_re"],
        "A_Lambda_im": _A_in["Lambda_im"],
        "A_B_re": _A_in["B_re"],
        "A_B_im": _A_in["B_im"],
        "A_C_re": _A_in["C_re"],
        "A_C_im": _A_in["C_im"],
        "A_log_dt": _A_in["log_dt"],
        "A_Dskip": _A_in["Dskip"],
        "B_x": _B_in["x"],
        "B_w1": _B_in["w1"],
        "B_w2": _B_in["w2"],
        "B_w3": _B_in["w3"],
        "B_w4": _B_in["w4"],
    }

def reference(A_x, A_Lambda_re, A_Lambda_im, A_B_re, A_B_im, A_C_re, A_C_im, A_log_dt, A_Dskip, B_x, B_w1, B_w2, B_w3, B_w4):
    def _A_ref(x, Lambda_re, Lambda_im, B_re, B_im, C_re, C_im, log_dt, Dskip):
        Bsz, L, H = x.shape
        Lam = Lambda_re + 1j * Lambda_im
        Bmat = B_re + 1j * B_im
        Cmat = C_re + 1j * C_im
        dt = torch.exp(log_dt)
        Lam_bar = torch.exp(dt * Lam)
        B_bar = ((Lam_bar - 1.0) / Lam)[:, None] * Bmat
        Bu = torch.einsum("bld,pd->blp", x + 0j, B_bar)
        h = torch.zeros_like(Bu[:, 0, :])
        hs = []
        for t in range(L):
            h = Lam_bar[None, :] * h + Bu[:, t, :]
            hs.append(h)
        hseq = torch.stack(hs, 1)
        y = 2.0 * torch.einsum("blp,dp->bld", hseq, Cmat).real + x * Dskip[None, None, :]
        return y

    def _B_ref(x, w1, w2, w3, w4):
        B, S, D = x.shape
        h = _gelu(_layernorm(x, axis=-1) @ w1)
        c = D // 4
        g0 = _pad(h[:, :, 0*c:1*c], ((0, 0), (1, 0), (0, 0)))[:, :S, :]
        g1 = _pad(h[:, :, 1*c:2*c], ((0, 0), (0, 1), (0, 0)))[:, 1:, :]
        g2 = _pad(h[:, :, 2*c:3*c], ((0, 0), (2, 0), (0, 0)))[:, :S, :]
        g3 = _pad(h[:, :, 3*c:   ], ((0, 0), (0, 2), (0, 0)))[:, 2:, :]
        hs = torch.concatenate([g0, g1, g2, g3], axis=-1) @ w2
        x1 = x + hs
        h2 = _gelu(_layernorm(x1, axis=-1) @ w3) @ w4
        return x1 + h2

    x = A_x
    xn = _layernorm(x, axis=-1)
    s = _A_ref(xn, A_Lambda_re, A_Lambda_im, A_B_re, A_B_im, A_C_re, A_C_im, A_log_dt, A_Dskip)
    g = _silu(_B_ref(xn, B_w1, B_w2, B_w3, B_w4))
    return x + s * g
```

```cpp
#include <cuda_runtime.h>
#include <cuda_bf16.h>
#include <cuda.h>
#include <stdint.h>

namespace {

constexpr int L_SEQ = 2048, DM = 512, FF = 1792;
constexpr int NT = 144, NH = 72;
constexpr int BLK = 138;
constexpr int NBLK = 15;
constexpr int CL = 8;
constexpr int ROWS_CP = 142;
constexpr int SLOT = NT * 128;
constexpr int CPB = ROWS_CP * 128;
constexpr int HALFB = NH * 128;
constexpr int WSLOTS = 6, WCH = 8192;
constexpr float LN_EPS = 1e-5f;
constexpr int PF_AFTER = 17;
constexpr int STAGGER = 230;

constexpr int SM_ACT = 0;
constexpr int SM_W = SM_ACT + 8 * SLOT;
constexpr int SM_STGA = SM_W + WSLOTS * WCH;
constexpr int SM_STGB = SM_STGA + SLOT;
constexpr int SM_TABA = SM_STGB + HALFB;
constexpr int SM_TABB = SM_TABA + NT * 8;
constexpr int SM_TAB3 = SM_TABB + NT * 8;
constexpr int SM_CHA = SM_TAB3 + NT * 8;
constexpr int SM_CHB = SM_CHA + 64 * 16;
constexpr int SM_CHC = SM_TAB3;
constexpr int SM_HP = SM_TAB3;
constexpr int SM_DSK = SM_CHB + 64 * 8;
constexpr int SM_BAR = SM_DSK + 256;
constexpr int B_WFULL = 0,
              B_AFULL = 108, B_X1 = 184, B_XF = 185, B_AH = 186,
              B_SAE = 194, B_SBE = 203, B_STORED = 207,
              B_WEMPTY = 214, B_STD = 220,
              B_SAF = 221, B_TAB = 230, B_SBF = 231, B_XR = 235, B_XE = 236, B_XP = 237,
              B_G = 238, B_AEMPTY = 239, B_ST1 = 240, B_ST3 = 241, NBAR = 242;
constexpr int NIMG = 9;
static_assert(CL * NT * 8 == HALFB, "ST3 byte count");
constexpr int SMEM_BYTES = SM_BAR + NBAR * 8;
static_assert(SMEM_BYTES <= 232448, "smem");

__device__ __align__(1024) unsigned char g_img[NBLK * CL * NIMG * SLOT];
__device__ __align__(16) unsigned long long g_end[NBLK * DM];
__device__ unsigned int g_epoch[NBLK * CL];

struct Params {
    CUtensorMap x, w[8], xn;
    const __nv_bfloat16 *xp, *lre, *lim, *ldt, *dsk;
    const unsigned char* pf[8];
    float* out;
};

__device__ __forceinline__ uint32_t smem_u32(const void* p) { return (uint32_t)__cvta_generic_to_shared(p); }
__device__ __forceinline__ void mbar_init(uint32_t bar, int cnt) {
    asm volatile("mbarrier.init.shared::cta.b64 [%0], %1;" ::"r"(bar), "r"(cnt) : "memory");
}
__device__ __forceinline__ void mbar_expect(uint32_t bar, uint32_t bytes) {
    asm volatile("mbarrier.arrive.expect_tx.shared::cta.b64 _, [%0], %1;" ::"r"(bar), "r"(bytes) : "memory");
}
__device__ __forceinline__ void mbar_arrive(uint32_t bar, uint32_t cnt) {
    asm volatile("mbarrier.arrive.shared::cta.b64 _, [%0], %1;" ::"r"(bar), "r"(cnt) : "memory");
}
__device__ __forceinline__ void mbar_wait(uint32_t bar, uint32_t parity) {
    asm volatile("{.reg .pred p; .reg .u32 c; mov.u32 c, 0x40000;\n"
                 "W: mbarrier.try_wait.parity.shared::cta.b64 p, [%0], %1; @p bra D;\n"
                 "sub.u32 c, c, 1; setp.ne.u32 p, c, 0; @p bra W;\n"
                 "D: }" ::"r"(bar), "r"(parity) : "memory");
}
__device__ __forceinline__ void mbar_wait_cluster(uint32_t bar) {
    asm volatile("{.reg .pred p; .reg .u32 c; mov.u32 c, 0x40000;\n"
                 "W: mbarrier.try_wait.parity.acquire.cluster.shared::cta.b64 p, [%0], 0; @p bra D;\n"
                 "sub.u32 c, c, 1; setp.ne.u32 p, c, 0; @p bra W;\n"
                 "D: }" ::"r"(bar) : "memory");
}
__device__ __forceinline__ uint32_t mapa(uint32_t a, uint32_t r) {
    uint32_t o;
    asm("mapa.shared::cluster.u32 %0, %1, %2;" : "=r"(o) : "r"(a), "r"(r));
    return o;
}
__device__ __forceinline__ void bar_sync(int id, int n) { __syncwarp(); asm volatile("bar.sync %0, %1;" ::"r"(id), "r"(n) : "memory"); }
__device__ __forceinline__ void fence_async() { asm volatile("fence.proxy.async.shared::cta;" ::: "memory"); }
__device__ __forceinline__ void tma2d(uint32_t dst, const CUtensorMap* m, int c0, int c1, uint32_t bar) {
    asm volatile("cp.async.bulk.tensor.2d.shared::cluster.global.mbarrier::complete_tx::bytes [%0], [%1, {%3, %4}], [%2];"
                 ::"r"(dst), "l"(m), "r"(bar), "r"(c0), "r"(c1) : "memory");
}
__device__ __forceinline__ void bulk_mc(uint32_t dst, const void* src, uint32_t bytes, uint32_t bar, uint16_t mask = 0xFF) {
    asm volatile("cp.async.bulk.shared::cluster.global.mbarrier::complete_tx::bytes.multicast::cluster [%0], [%1], %2, [%3], %4;"
                 ::"r"(dst), "l"(src), "r"(bytes), "r"(bar), "h"(mask) : "memory");
}
__device__ __forceinline__ void wait_tma2d(uint32_t eb, uint32_t parity, uint32_t dst, const CUtensorMap* m, int c0, int c1, uint32_t bar) {
    asm volatile("{.reg .pred p; .reg .u32 c; mov.u32 c, 0x40000;\n"
                 "W: mbarrier.try_wait.parity.shared::cta.b64 p, [%5], %6; @p bra D;\n"
                 "sub.u32 c, c, 1; setp.ne.u32 p, c, 0; @p bra W;\n"
                 "D: elect.sync _|p, 0xFFFFFFFF;\n"
                 "@p cp.async.bulk.tensor.2d.shared::cluster.global.mbarrier::complete_tx::bytes [%0], [%1, {%3, %4}], [%2];}"
                 ::"r"(dst), "l"(m), "r"(bar), "r"(c0), "r"(c1), "r"(eb), "r"(parity) : "memory");
}
__device__ __forceinline__ void wait_bulk_mc(uint32_t eb, uint32_t parity, uint32_t dst, const void* src, uint32_t bytes, uint32_t bar) {
    asm volatile("{.reg .pred p; .reg .u32 c; mov.u32 c, 0x40000;\n"
                 "W: mbarrier.try_wait.parity.shared::cta.b64 p, [%5], %6; @p bra D;\n"
                 "sub.u32 c, c, 1; setp.ne.u32 p, c, 0; @p bra W;\n"
                 "D: elect.sync _|p, 0xFFFFFFFF;\n"
                 "@p cp.async.bulk.shared::cluster.global.mbarrier::complete_tx::bytes.multicast::cluster [%0], [%1], %2, [%3], %4;}"
                 ::"r"(dst), "l"(src), "r"(bytes), "r"(bar), "h"((uint16_t)0xFF), "r"(eb), "r"(parity) : "memory");
}
__device__ __forceinline__ void bulk_store(void* dst, uint32_t src, uint32_t bytes) {
    asm volatile("cp.async.bulk.global.shared::cta.bulk_group [%0], [%1], %2;" ::"l"(dst), "r"(src), "r"(bytes) : "memory");
}
__device__ __forceinline__ void st_async2(uint32_t addr, float a, float b, uint32_t bar) {
    asm volatile("st.async.weak.shared::cluster.mbarrier::complete_tx::bytes.v2.f32 [%0], {%1, %2}, [%3];"
                 ::"r"(addr), "f"(a), "f"(b), "r"(bar) : "memory");
}
__device__ __forceinline__ void stsm4t(uint32_t a, uint32_t r0, uint32_t r1, uint32_t r2, uint32_t r3) {
    asm volatile("stmatrix.sync.aligned.m8n8.x4.trans.shared.b16 [%0], {%1, %2, %3, %4};" ::"r"(a), "r"(r0), "r"(r1), "r"(r2), "r"(r3));
}
__device__ __forceinline__ void stsm2t(uint32_t a, uint32_t r0, uint32_t r1) {
    asm volatile("stmatrix.sync.aligned.m8n8.x2.trans.shared.b16 [%0], {%1, %2};" ::"r"(a), "r"(r0), "r"(r1));
}
__device__ __forceinline__ void ldsm4t(uint32_t a, uint32_t& r0, uint32_t& r1, uint32_t& r2, uint32_t& r3) {
    asm volatile("ldmatrix.sync.aligned.m8n8.x4.trans.shared.b16 {%0, %1, %2, %3}, [%4];" : "=r"(r0), "=r"(r1), "=r"(r2), "=r"(r3) : "r"(a) : "memory");
}
extern __shared__ __align__(1024) unsigned char smem[];
__device__ __forceinline__ float4 lds128(uint32_t off) { return *reinterpret_cast<const float4*>(smem + off); }
__device__ __forceinline__ float2 lds64(uint32_t off) { return *reinterpret_cast<const float2*>(smem + off); }
__device__ __forceinline__ uint32_t pack2(float lo, float hi) {
    uint32_t r;
    asm("cvt.rn.bf16x2.f32 %0, %1, %2;" : "=r"(r) : "f"(hi), "f"(lo));
    return r;
}
__device__ __forceinline__ float bf_lo(uint32_t v) { return __uint_as_float(v << 16); }
__device__ __forceinline__ float bf_hi(uint32_t v) { return __uint_as_float(v & 0xFFFF0000u); }
__device__ __forceinline__ float gelu_h(float hz) {
    const float w = hz * fmaf(hz * hz, 8.0f * 0.0356774081f, 2.0f * 0.7978845608f);
    float th;
    asm("tanh.approx.f32 %0, %1;" : "=f"(th) : "f"(w));
    return fmaf(hz, th, hz);
}

__device__ __forceinline__ void kloop_s(float (&d)[72], uint32_t wb, uint32_t ab, uint32_t da, uint32_t db, uint32_t eb, uint32_t es,
              uint32_t e0, uint32_t cnt, uint32_t dw0, uint32_t acc, uint32_t w0, uint32_t ord, uint32_t nch, uint32_t db0, uint32_t pre) {
    asm volatile(
        "{\n"
        ".reg .pred pr, p0, p1, pa, pt, pe, pf, pk, pw;\n"
        ".reg .u32 k, wb, ab, da, db, eb, pb, pc, cb, c, t0, t1, hi, hb, dwe, dbe, em, we;\n"
        ".reg .u64 dA, dB;\n"
        "mov.u32 wb, %72; mov.u32 ab, %73; mov.u32 da, %74; mov.u32 db, %75; mov.u32 eb, %76; mov.u32 pb, eb; mov.u32 pc, eb;\n"
        "mov.u32 hi, %%ctaid.y; add.u32 hi, hi, 0x40000040; mov.u32 hb, %%ctaid.z; add.u32 hb, hb, 1073741888; add.u32 dwe, %80, 3072; mov.u32 k, 0; setp.eq.u32 pt, k, 0; setp.ne.u32 pr, k, 0; setp.ne.u32 pe, k, 0; setp.ne.u32 pf, k, 0;\n"
        "setp.ne.u32 pw, %82, 0; setp.ne.u32 pa, %81, 0;\n"
        "add.u32 dbe, %85, 9216; shl.b32 em, %77, 3; not.b32 em, em; @pw mov.u32 em, 0xFFFFFFFF; mad.lo.u32 we, %84, 8, wb;\n"
        "LOOP:\n"
        "@pr bra.uni GO;\n"
        "mov.u32 c, 0x40000;\n"
        "W0: mbarrier.try_wait.parity.shared::cta.b64 p0, [wb], 0; @p0 bra.uni D0;\n"
        "sub.u32 c, c, 1; setp.ne.u32 p0, c, 0; @p0 bra.uni W0;\n"
        "D0:\n"
        "mov.u32 c, 0x40000;\n"
        "W1: mbarrier.try_wait.parity.shared::cta.b64 p0, [ab], 0; @p0 bra.uni D1;\n"
        "sub.u32 c, c, 1; setp.ne.u32 p0, c, 0; @p0 bra.uni W1;\n"
        "D1:\n"
        "setp.eq.u32 pk, wb, %72; setp.ne.and.u32 pk, %86, 0, pk; @pk bar.sync %86, 256;\n"
        "GO:\n"
        "add.u32 wb, wb, 8; add.u32 ab, ab, 8;\n"
        "mbarrier.test_wait.parity.shared::cta.b64 p0, [wb], 0; mbarrier.test_wait.parity.shared::cta.b64 p1, [ab], 0;\n"
        "wgmma.fence.sync.aligned;\n"
        "add.u32 t0, da, 0; add.u32 t1, db, 0; mov.b64 dA, {t0, hi}; mov.b64 dB, {t1, hb};\n"
        "wgmma.mma_async.sync.aligned.m64n144k16.f32.bf16.bf16 {%0, %1, %2, %3, %4, %5, %6, %7, %8, %9, %10, %11, %12, %13, %14, %15, %16, %17, %18, %19, %20, %21, %22, %23, %24, %25, %26, %27, %28, %29, %30, %31, %32, %33, %34, %35, %36, %37, %38, %39, %40, %41, %42, %43, %44, %45, %46, %47, %48, %49, %50, %51, %52, %53, %54, %55, %56, %57, %58, %59, %60, %61, %62, %63, %64, %65, %66, %67, %68, %69, %70, %71}, dA, dB, pa, 1, 1, 0, 0;\n"
        "add.u32 t0, da, 2; add.u32 t1, db, 2; mov.b64 dA, {t0, hi}; mov.b64 dB, {t1, hb};\n"
        "wgmma.mma_async.sync.aligned.m64n144k16.f32.bf16.bf16 {%0, %1, %2, %3, %4, %5, %6, %7, %8, %9, %10, %11, %12, %13, %14, %15, %16, %17, %18, %19, %20, %21, %22, %23, %24, %25, %26, %27, %28, %29, %30, %31, %32, %33, %34, %35, %36, %37, %38, %39, %40, %41, %42, %43, %44, %45, %46, %47, %48, %49, %50, %51, %52, %53, %54, %55, %56, %57, %58, %59, %60, %61, %62, %63, %64, %65, %66, %67, %68, %69, %70, %71}, dA, dB, pt, 1, 1, 0, 0;\n"
        "add.u32 t0, da, 4; add.u32 t1, db, 4; mov.b64 dA, {t0, hi}; mov.b64 dB, {t1, hb};\n"
        "wgmma.mma_async.sync.aligned.m64n144k16.f32.bf16.bf16 {%0, %1, %2, %3, %4, %5, %6, %7, %8, %9, %10, %11, %12, %13, %14, %15, %16, %17, %18, %19, %20, %21, %22, %23, %24, %25, %26, %27, %28, %29, %30, %31, %32, %33, %34, %35, %36, %37, %38, %39, %40, %41, %42, %43, %44, %45, %46, %47, %48, %49, %50, %51, %52, %53, %54, %55, %56, %57, %58, %59, %60, %61, %62, %63, %64, %65, %66, %67, %68, %69, %70, %71}, dA, dB, pt, 1, 1, 0, 0;\n"
        "add.u32 t0, da, 6; add.u32 t1, db, 6; mov.b64 dA, {t0, hi}; mov.b64 dB, {t1, hb};\n"
        "wgmma.mma_async.sync.aligned.m64n144k16.f32.bf16.bf16 {%0, %1, %2, %3, %4, %5, %6, %7, %8, %9, %10, %11, %12, %13, %14, %15, %16, %17, %18, %19, %20, %21, %22, %23, %24, %25, %26, %27, %28, %29, %30, %31, %32, %33, %34, %35, %36, %37, %38, %39, %40, %41, %42, %43, %44, %45, %46, %47, %48, %49, %50, %51, %52, %53, %54, %55, %56, %57, %58, %59, %60, %61, %62, %63, %64, %65, %66, %67, %68, %69, %70, %71}, dA, dB, pt, 1, 1, 0, 0;\n"
        "wgmma.commit_group.sync.aligned;\n"
        "setp.eq.u32 pa, k, k;\n"
        "mov.u32 cb, eb; add.u32 da, da, 512; add.u32 db, db, 1152; add.u32 eb, eb, %77;\n"
        "setp.eq.u32 pk, da, dwe; @pk mov.u32 da, %80; and.pred pk, pk, pw; @pk mov.u32 eb, %78;\n"
        "wgmma.wait_group.sync.aligned 1;\n"
        "@pe mbarrier.arrive.shared::cluster.b64 _, [pb], %79;\n"
        "mov.u32 pb, cb; and.pred pr, p0, p1;\n"
        "setp.ne.u32 pe, %79, 0;\n"
        "setp.ne.u32 pk, wb, we; @pk bra.uni LOOP;\n"
        "wgmma.wait_group.sync.aligned 0;\n"
        "@pe mbarrier.arrive.shared::cluster.b64 _, [pb], %79;\n"
        "}\n"
        :
          "+f"(d[0]), "+f"(d[1]), "+f"(d[2]), "+f"(d[3]), "+f"(d[4]), "+f"(d[5]), "+f"(d[6]), "+f"(d[7]),
          "+f"(d[8]), "+f"(d[9]), "+f"(d[10]), "+f"(d[11]), "+f"(d[12]), "+f"(d[13]), "+f"(d[14]), "+f"(d[15]),
          "+f"(d[16]), "+f"(d[17]), "+f"(d[18]), "+f"(d[19]), "+f"(d[20]), "+f"(d[21]), "+f"(d[22]), "+f"(d[23]),
          "+f"(d[24]), "+f"(d[25]), "+f"(d[26]), "+f"(d[27]), "+f"(d[28]), "+f"(d[29]), "+f"(d[30]), "+f"(d[31]),
          "+f"(d[32]), "+f"(d[33]), "+f"(d[34]), "+f"(d[35]), "+f"(d[36]), "+f"(d[37]), "+f"(d[38]), "+f"(d[39]),
          "+f"(d[40]), "+f"(d[41]), "+f"(d[42]), "+f"(d[43]), "+f"(d[44]), "+f"(d[45]), "+f"(d[46]), "+f"(d[47]),
          "+f"(d[48]), "+f"(d[49]), "+f"(d[50]), "+f"(d[51]), "+f"(d[52]), "+f"(d[53]), "+f"(d[54]), "+f"(d[55]),
          "+f"(d[56]), "+f"(d[57]), "+f"(d[58]), "+f"(d[59]), "+f"(d[60]), "+f"(d[61]), "+f"(d[62]), "+f"(d[63]),
          "+f"(d[64]), "+f"(d[65]), "+f"(d[66]), "+f"(d[67]), "+f"(d[68]), "+f"(d[69]), "+f"(d[70]), "+f"(d[71])
        : "r"(wb), "r"(ab), "r"(da), "r"(db), "r"(eb), "r"(es), "r"(e0), "r"(cnt), "r"(dw0), "r"(acc), "r"(w0), "r"(ord), "r"(nch), "r"(db0), "r"(pre)
        : "memory");
}

__device__ __forceinline__ void kloop_h(float (&d)[72], uint32_t wb, uint32_t ab, uint32_t da, uint32_t db, uint32_t eb, uint32_t es,
              uint32_t e0, uint32_t cnt, uint32_t dw0, uint32_t acc, uint32_t w0, uint32_t ord, uint32_t nch, uint32_t db0, uint32_t pre) {
    asm volatile(
        "{\n"
        ".reg .pred pr, p0, p1, p2, p3, pa, pt, pe, pk, pw;\n"
        ".reg .u32 wb, ab, da, db, eb, pb, cb, c, t0, t1, hi, hb, dwe, dbe, em, we;\n"
        ".reg .u64 dA, dB;\n"
        "mov.u32 wb, %36; mov.u32 ab, %37; mov.u32 da, %38; mov.u32 db, %39; mov.u32 eb, %40; mov.u32 pb, eb;\n"
        "mov.u32 hi, %%ctaid.y; add.u32 hi, hi, 0x40000040; mov.u32 hb, %%ctaid.z; add.u32 hb, hb, 1073741888;\n"
        "add.u32 dwe, %44, 3072; setp.eq.u32 pt, wb, wb; setp.ne.u32 pr, wb, wb; setp.ne.u32 pe, wb, wb;\n"
        "setp.ne.u32 pw, %46, 0; setp.ne.u32 pa, %45, 0;\n"
        "add.u32 dbe, %49, 9216; shl.b32 em, %41, 2; not.b32 em, em; @pw mov.u32 em, 0xFFFFFFFF; mad.lo.u32 we, %48, 8, wb;\n"
        "LOOP:\n"
        "@pr bra.uni GO;\n"
        "mov.u32 c, 0x40000;\n"
        "W0: mbarrier.try_wait.parity.shared::cta.b64 p0, [wb], 0; @p0 bra.uni D0;\n"
        "sub.u32 c, c, 1; setp.ne.u32 p0, c, 0; @p0 bra.uni W0;\n"
        "D0:\n"
        "mov.u32 c, 0x40000;\n"
        "W1: mbarrier.try_wait.parity.shared::cta.b64 p0, [wb + 8], 0; @p0 bra.uni D1;\n"
        "sub.u32 c, c, 1; setp.ne.u32 p0, c, 0; @p0 bra.uni W1;\n"
        "D1:\n"
        "mov.u32 c, 0x40000;\n"
        "W2: mbarrier.try_wait.parity.shared::cta.b64 p0, [ab], 0; @p0 bra.uni D2;\n"
        "sub.u32 c, c, 1; setp.ne.u32 p0, c, 0; @p0 bra.uni W2;\n"
        "D2:\n"
        "mov.u32 c, 0x40000;\n"
        "W3: mbarrier.try_wait.parity.shared::cta.b64 p0, [ab + 8], 0; @p0 bra.uni D3;\n"
        "sub.u32 c, c, 1; setp.ne.u32 p0, c, 0; @p0 bra.uni W3;\n"
        "D3:\n"
        "GO:\n"
        "add.u32 wb, wb, 16; add.u32 ab, ab, 16;\n"
        "wgmma.fence.sync.aligned;\n"
        "add.u32 t0, da, 0; add.u32 t1, db, 0; mov.b64 dA, {t0, hi}; mov.b64 dB, {t1, hb};\n"
        "wgmma.mma_async.sync.aligned.m64n72k16.f32.bf16.bf16 {%0, %1, %2, %3, %4, %5, %6, %7, %8, %9, %10, %11, %12, %13, %14, %15, %16, %17, %18, %19, %20, %21, %22, %23, %24, %25, %26, %27, %28, %29, %30, %31, %32, %33, %34, %35}, dA, dB, pa, 1, 1, 1, 0;\n"
        "add.u32 t0, da, 128; add.u32 t1, db, 2; mov.b64 dA, {t0, hi}; mov.b64 dB, {t1, hb};\n"
        "wgmma.mma_async.sync.aligned.m64n72k16.f32.bf16.bf16 {%0, %1, %2, %3, %4, %5, %6, %7, %8, %9, %10, %11, %12, %13, %14, %15, %16, %17, %18, %19, %20, %21, %22, %23, %24, %25, %26, %27, %28, %29, %30, %31, %32, %33, %34, %35}, dA, dB, pt, 1, 1, 1, 0;\n"
        "add.u32 t0, da, 256; add.u32 t1, db, 4; mov.b64 dA, {t0, hi}; mov.b64 dB, {t1, hb};\n"
        "wgmma.mma_async.sync.aligned.m64n72k16.f32.bf16.bf16 {%0, %1, %2, %3, %4, %5, %6, %7, %8, %9, %10, %11, %12, %13, %14, %15, %16, %17, %18, %19, %20, %21, %22, %23, %24, %25, %26, %27, %28, %29, %30, %31, %32, %33, %34, %35}, dA, dB, pt, 1, 1, 1, 0;\n"
        "add.u32 t0, da, 384; add.u32 t1, db, 6; mov.b64 dA, {t0, hi}; mov.b64 dB, {t1, hb};\n"
        "wgmma.mma_async.sync.aligned.m64n72k16.f32.bf16.bf16 {%0, %1, %2, %3, %4, %5, %6, %7, %8, %9, %10, %11, %12, %13, %14, %15, %16, %17, %18, %19, %20, %21, %22, %23, %24, %25, %26, %27, %28, %29, %30, %31, %32, %33, %34, %35}, dA, dB, pt, 1, 1, 1, 0;\n"
        "add.u32 t0, da, 512; add.u32 t1, db, 1152; mov.b64 dA, {t0, hi}; mov.b64 dB, {t1, hb};\n"
        "wgmma.mma_async.sync.aligned.m64n72k16.f32.bf16.bf16 {%0, %1, %2, %3, %4, %5, %6, %7, %8, %9, %10, %11, %12, %13, %14, %15, %16, %17, %18, %19, %20, %21, %22, %23, %24, %25, %26, %27, %28, %29, %30, %31, %32, %33, %34, %35}, dA, dB, pt, 1, 1, 1, 0;\n"
        "add.u32 t0, da, 640; add.u32 t1, db, 1154; mov.b64 dA, {t0, hi}; mov.b64 dB, {t1, hb};\n"
        "wgmma.mma_async.sync.aligned.m64n72k16.f32.bf16.bf16 {%0, %1, %2, %3, %4, %5, %6, %7, %8, %9, %10, %11, %12, %13, %14, %15, %16, %17, %18, %19, %20, %21, %22, %23, %24, %25, %26, %27, %28, %29, %30, %31, %32, %33, %34, %35}, dA, dB, pt, 1, 1, 1, 0;\n"
        "add.u32 t0, da, 768; add.u32 t1, db, 1156; mov.b64 dA, {t0, hi}; mov.b64 dB, {t1, hb};\n"
        "wgmma.mma_async.sync.aligned.m64n72k16.f32.bf16.bf16 {%0, %1, %2, %3, %4, %5, %6, %7, %8, %9, %10, %11, %12, %13, %14, %15, %16, %17, %18, %19, %20, %21, %22, %23, %24, %25, %26, %27, %28, %29, %30, %31, %32, %33, %34, %35}, dA, dB, pt, 1, 1, 1, 0;\n"
        "add.u32 t0, da, 896; add.u32 t1, db, 1158; mov.b64 dA, {t0, hi}; mov.b64 dB, {t1, hb};\n"
        "wgmma.mma_async.sync.aligned.m64n72k16.f32.bf16.bf16 {%0, %1, %2, %3, %4, %5, %6, %7, %8, %9, %10, %11, %12, %13, %14, %15, %16, %17, %18, %19, %20, %21, %22, %23, %24, %25, %26, %27, %28, %29, %30, %31, %32, %33, %34, %35}, dA, dB, pt, 1, 1, 1, 0;\n"
        "wgmma.commit_group.sync.aligned;\n"
        "setp.eq.u32 pa, wb, wb;\n"
        "mov.u32 cb, eb; add.u32 da, da, 1024; add.u32 db, db, 2304; add.u32 eb, eb, %41;\n"
        "setp.eq.u32 pk, da, dwe; @pk mov.u32 da, %44; and.pred pk, pk, pw; @pk mov.u32 eb, %42;\n"
        "wgmma.wait_group.sync.aligned 1;\n"
        "@pe mbarrier.arrive.shared::cluster.b64 _, [pb], %43;\n"
        "mbarrier.test_wait.parity.shared::cta.b64 p0, [wb], 0; mbarrier.test_wait.parity.shared::cta.b64 p1, [wb + 8], 0;\n"
        "mbarrier.test_wait.parity.shared::cta.b64 p2, [ab], 0; mbarrier.test_wait.parity.shared::cta.b64 p3, [ab + 8], 0;\n"
        "mov.u32 pb, cb;\n"
        "setp.ne.u32 pe, %43, 0;\n"
        "and.pred p0, p0, p1; and.pred p2, p2, p3; and.pred pr, p0, p2;\n"
        "setp.ne.u32 pk, wb, we; @pk bra.uni LOOP;\n"
        "setp.ne.u32 pk, %47, 0; @pk bar.arrive %47, 256;\n"
        "wgmma.wait_group.sync.aligned 0;\n"
        "@pe mbarrier.arrive.shared::cluster.b64 _, [pb], %43;\n"
        "}\n"
        :
          "+f"(d[0]), "+f"(d[1]), "+f"(d[2]), "+f"(d[3]), "+f"(d[4]), "+f"(d[5]), "+f"(d[6]), "+f"(d[7]),
          "+f"(d[8]), "+f"(d[9]), "+f"(d[10]), "+f"(d[11]), "+f"(d[12]), "+f"(d[13]), "+f"(d[14]), "+f"(d[15]),
          "+f"(d[16]), "+f"(d[17]), "+f"(d[18]), "+f"(d[19]), "+f"(d[20]), "+f"(d[21]), "+f"(d[22]), "+f"(d[23]),
          "+f"(d[24]), "+f"(d[25]), "+f"(d[26]), "+f"(d[27]), "+f"(d[28]), "+f"(d[29]), "+f"(d[30]), "+f"(d[31]),
          "+f"(d[32]), "+f"(d[33]), "+f"(d[34]), "+f"(d[35])
        : "r"(wb), "r"(ab), "r"(da), "r"(db), "r"(eb), "r"(es), "r"(e0), "r"(cnt), "r"(dw0), "r"(acc), "r"(w0), "r"(ord), "r"(nch), "r"(db0), "r"(pre)
        : "memory");
}

__device__ __forceinline__ void kloop_f(float (&d)[72], uint32_t wb, uint32_t ab, uint32_t da, uint32_t db, uint32_t eb, uint32_t es,
              uint32_t e0, uint32_t cnt, uint32_t dw0, uint32_t acc, uint32_t w0, uint32_t ord, uint32_t nch, uint32_t db0, uint32_t pre) {
    asm volatile(
        "{\n"
        ".reg .pred pr, p0, p1, pa, pt, pe, pf, pk, pw;\n"
        ".reg .u32 k, wb, ab, da, db, eb, pb, pc, cb, c, t0, t1, hi, hb, dwe, dbe, em, we;\n"
        ".reg .u64 dA, dB;\n"
        "mov.u32 wb, %72; mov.u32 ab, %73; mov.u32 da, %74; mov.u32 db, %75; mov.u32 eb, %76; mov.u32 pb, eb; mov.u32 pc, eb;\n"
        "mov.u32 hi, %%ctaid.y; add.u32 hi, hi, 0x40000040; mov.u32 hb, %%ctaid.z; add.u32 hb, hb, 1073741888; add.u32 dwe, %80, 3072; mov.u32 k, 0; setp.eq.u32 pt, k, 0; setp.ne.u32 pr, k, 0; setp.ne.u32 pe, k, 0; setp.ne.u32 pf, k, 0;\n"
        "setp.ne.u32 pw, %82, 0; setp.ne.u32 pa, %81, 0;\n"
        "add.u32 dbe, %85, 9216; shl.b32 em, %77, 3; not.b32 em, em; @pw mov.u32 em, 0xFFFFFFFF; mad.lo.u32 we, %84, 8, wb;\n"
        "LOOP:\n"
        "@pr bra.uni GO;\n"
        "mov.u32 c, 0x40000;\n"
        "W0: mbarrier.try_wait.parity.shared::cta.b64 p0, [wb], 0; @p0 bra.uni D0;\n"
        "sub.u32 c, c, 1; setp.ne.u32 p0, c, 0; @p0 bra.uni W0;\n"
        "D0:\n"
        "mov.u32 c, 0x40000;\n"
        "W1: mbarrier.try_wait.parity.shared::cta.b64 p0, [ab], 0; @p0 bra.uni D1;\n"
        "sub.u32 c, c, 1; setp.ne.u32 p0, c, 0; @p0 bra.uni W1;\n"
        "D1:\n"
        "setp.eq.u32 pk, wb, %72; setp.ne.and.u32 pk, %86, 0, pk; setp.eq.u32 p0, %86, 3; selp.u32 t0, 160, 256, p0; @pk bar.sync %86, t0;\n"
        "GO:\n"
        "add.u32 wb, wb, 8; add.u32 ab, ab, 8;\n"
        "mbarrier.test_wait.parity.shared::cta.b64 p0, [wb], 0; mbarrier.test_wait.parity.shared::cta.b64 p1, [ab], 0;\n"
        "wgmma.fence.sync.aligned;\n"
        "add.u32 t0, da, 0; add.u32 t1, db, 0; mov.b64 dA, {t0, hi}; mov.b64 dB, {t1, hb};\n"
        "wgmma.mma_async.sync.aligned.m64n144k16.f32.bf16.bf16 {%0, %1, %2, %3, %4, %5, %6, %7, %8, %9, %10, %11, %12, %13, %14, %15, %16, %17, %18, %19, %20, %21, %22, %23, %24, %25, %26, %27, %28, %29, %30, %31, %32, %33, %34, %35, %36, %37, %38, %39, %40, %41, %42, %43, %44, %45, %46, %47, %48, %49, %50, %51, %52, %53, %54, %55, %56, %57, %58, %59, %60, %61, %62, %63, %64, %65, %66, %67, %68, %69, %70, %71}, dA, dB, pa, 1, 1, 1, 0;\n"
        "add.u32 t0, da, 128; add.u32 t1, db, 2; mov.b64 dA, {t0, hi}; mov.b64 dB, {t1, hb};\n"
        "wgmma.mma_async.sync.aligned.m64n144k16.f32.bf16.bf16 {%0, %1, %2, %3, %4, %5, %6, %7, %8, %9, %10, %11, %12, %13, %14, %15, %16, %17, %18, %19, %20, %21, %22, %23, %24, %25, %26, %27, %28, %29, %30, %31, %32, %33, %34, %35, %36, %37, %38, %39, %40, %41, %42, %43, %44, %45, %46, %47, %48, %49, %50, %51, %52, %53, %54, %55, %56, %57, %58, %59, %60, %61, %62, %63, %64, %65, %66, %67, %68, %69, %70, %71}, dA, dB, pt, 1, 1, 1, 0;\n"
        "add.u32 t0, da, 256; add.u32 t1, db, 4; mov.b64 dA, {t0, hi}; mov.b64 dB, {t1, hb};\n"
        "wgmma.mma_async.sync.aligned.m64n144k16.f32.bf16.bf16 {%0, %1, %2, %3, %4, %5, %6, %7, %8, %9, %10, %11, %12, %13, %14, %15, %16, %17, %18, %19, %20, %21, %22, %23, %24, %25, %26, %27, %28, %29, %30, %31, %32, %33, %34, %35, %36, %37, %38, %39, %40, %41, %42, %43, %44, %45, %46, %47, %48, %49, %50, %51, %52, %53, %54, %55, %56, %57, %58, %59, %60, %61, %62, %63, %64, %65, %66, %67, %68, %69, %70, %71}, dA, dB, pt, 1, 1, 1, 0;\n"
        "add.u32 t0, da, 384; add.u32 t1, db, 6; mov.b64 dA, {t0, hi}; mov.b64 dB, {t1, hb};\n"
        "wgmma.mma_async.sync.aligned.m64n144k16.f32.bf16.bf16 {%0, %1, %2, %3, %4, %5, %6, %7, %8, %9, %10, %11, %12, %13, %14, %15, %16, %17, %18, %19, %20, %21, %22, %23, %24, %25, %26, %27, %28, %29, %30, %31, %32, %33, %34, %35, %36, %37, %38, %39, %40, %41, %42, %43, %44, %45, %46, %47, %48, %49, %50, %51, %52, %53, %54, %55, %56, %57, %58, %59, %60, %61, %62, %63, %64, %65, %66, %67, %68, %69, %70, %71}, dA, dB, pt, 1, 1, 1, 0;\n"
        "wgmma.commit_group.sync.aligned;\n"
        "setp.eq.u32 pa, k, k;\n"
        "mov.u32 cb, eb; add.u32 da, da, 512; add.u32 db, db, 1152; add.u32 eb, eb, %77;\n"
        "setp.eq.u32 pk, da, dwe; @pk mov.u32 da, %80; and.pred pk, pk, pw; @pk mov.u32 eb, %78;\n"
        "and.b32 eb, eb, em; setp.eq.u32 pk, dbe, db; @pk mov.u32 db, %85;\n"
        "wgmma.wait_group.sync.aligned 1;\n"
        "@pe mbarrier.arrive.shared::cluster.b64 _, [pb], %79;\n"
        "mov.u32 pb, cb; and.pred pr, p0, p1;\n"
        "setp.ne.u32 pe, %79, 0;\n"
        "setp.ne.u32 pk, wb, we; @pk bra.uni LOOP;\n"
        "setp.ne.u32 pk, %83, 0; @pk bar.arrive %83, 256;\n"
        "wgmma.wait_group.sync.aligned 0;\n"
        "@pe mbarrier.arrive.shared::cluster.b64 _, [pb], %79;\n"
        "}\n"
        :
          "+f"(d[0]), "+f"(d[1]), "+f"(d[2]), "+f"(d[3]), "+f"(d[4]), "+f"(d[5]), "+f"(d[6]), "+f"(d[7]),
          "+f"(d[8]), "+f"(d[9]), "+f"(d[10]), "+f"(d[11]), "+f"(d[12]), "+f"(d[13]), "+f"(d[14]), "+f"(d[15]),
          "+f"(d[16]), "+f"(d[17]), "+f"(d[18]), "+f"(d[19]), "+f"(d[20]), "+f"(d[21]), "+f"(d[22]), "+f"(d[23]),
          "+f"(d[24]), "+f"(d[25]), "+f"(d[26]), "+f"(d[27]), "+f"(d[28]), "+f"(d[29]), "+f"(d[30]), "+f"(d[31]),
          "+f"(d[32]), "+f"(d[33]), "+f"(d[34]), "+f"(d[35]), "+f"(d[36]), "+f"(d[37]), "+f"(d[38]), "+f"(d[39]),
          "+f"(d[40]), "+f"(d[41]), "+f"(d[42]), "+f"(d[43]), "+f"(d[44]), "+f"(d[45]), "+f"(d[46]), "+f"(d[47]),
          "+f"(d[48]), "+f"(d[49]), "+f"(d[50]), "+f"(d[51]), "+f"(d[52]), "+f"(d[53]), "+f"(d[54]), "+f"(d[55]),
          "+f"(d[56]), "+f"(d[57]), "+f"(d[58]), "+f"(d[59]), "+f"(d[60]), "+f"(d[61]), "+f"(d[62]), "+f"(d[63]),
          "+f"(d[64]), "+f"(d[65]), "+f"(d[66]), "+f"(d[67]), "+f"(d[68]), "+f"(d[69]), "+f"(d[70]), "+f"(d[71])
        : "r"(wb), "r"(ab), "r"(da), "r"(db), "r"(eb), "r"(es), "r"(e0), "r"(cnt), "r"(dw0), "r"(acc), "r"(w0), "r"(ord), "r"(nch), "r"(db0), "r"(pre)
        : "memory");
}

__device__ __forceinline__ void kloop_c(float (&d)[72], uint32_t wb, uint32_t ab, uint32_t da, uint32_t db, uint32_t eb, uint32_t es,
              uint32_t e0, uint32_t cnt, uint32_t dw0, uint32_t acc, uint32_t w0, uint32_t ord, uint32_t nch, uint32_t db0, uint32_t pre) {
    asm volatile(
        "{\n"
        ".reg .pred pr, p0, p1, pa, pt, pe, pf, pk, pw;\n"
        ".reg .u32 k, wb, ab, da, db, eb, pb, pc, cb, c, t0, t1, hi, hb, dwe, dbe, em, we;\n"
        ".reg .u64 dA, dB;\n"
        "mov.u32 wb, %72; mov.u32 ab, %73; mov.u32 da, %74; mov.u32 db, %75; mov.u32 eb, %76; mov.u32 pb, eb; mov.u32 pc, eb;\n"
        "mov.u32 hi, %%ctaid.y; add.u32 hi, hi, 0x40000040; mov.u32 hb, %%ctaid.z; add.u32 hb, hb, 8; add.u32 dwe, %80, 3072; mov.u32 k, 0; setp.eq.u32 pt, k, 0; setp.ne.u32 pr, k, 0; setp.ne.u32 pe, k, 0; setp.ne.u32 pf, k, 0;\n"
        "setp.ne.u32 pw, %82, 0; setp.ne.u32 pa, %81, 0;\n"
        "add.u32 dbe, %85, 9216; shl.b32 em, %77, 3; not.b32 em, em; @pw mov.u32 em, 0xFFFFFFFF; mad.lo.u32 we, %84, 8, wb;\n"
        "LOOP:\n"
        "@pr bra.uni GO;\n"
        "mov.u32 c, 0x40000;\n"
        "W0: mbarrier.try_wait.parity.shared::cta.b64 p0, [wb], 0; @p0 bra.uni D0;\n"
        "sub.u32 c, c, 1; setp.ne.u32 p0, c, 0; @p0 bra.uni W0;\n"
        "D0:\n"
        "mov.u32 c, 0x40000;\n"
        "W1: mbarrier.try_wait.parity.shared::cta.b64 p0, [ab], 0; @p0 bra.uni D1;\n"
        "sub.u32 c, c, 1; setp.ne.u32 p0, c, 0; @p0 bra.uni W1;\n"
        "D1:\n"
        "GO:\n"
        "add.u32 wb, wb, 8; add.u32 ab, ab, 8;\n"
        "mbarrier.test_wait.parity.shared::cta.b64 p0, [wb], 0; mbarrier.test_wait.parity.shared::cta.b64 p1, [ab], 0;\n"
        "wgmma.fence.sync.aligned;\n"
        "add.u32 t0, da, 0; add.u32 t1, db, 0; mov.b64 dA, {t0, hi}; mov.b64 dB, {t1, hb};\n"
        "wgmma.mma_async.sync.aligned.m64n144k16.f32.bf16.bf16 {%0, %1, %2, %3, %4, %5, %6, %7, %8, %9, %10, %11, %12, %13, %14, %15, %16, %17, %18, %19, %20, %21, %22, %23, %24, %25, %26, %27, %28, %29, %30, %31, %32, %33, %34, %35, %36, %37, %38, %39, %40, %41, %42, %43, %44, %45, %46, %47, %48, %49, %50, %51, %52, %53, %54, %55, %56, %57, %58, %59, %60, %61, %62, %63, %64, %65, %66, %67, %68, %69, %70, %71}, dA, dB, pa, 1, 1, 0, 1;\n"
        "add.u32 t0, da, 2; add.u32 t1, db, 288; mov.b64 dA, {t0, hi}; mov.b64 dB, {t1, hb};\n"
        "wgmma.mma_async.sync.aligned.m64n144k16.f32.bf16.bf16 {%0, %1, %2, %3, %4, %5, %6, %7, %8, %9, %10, %11, %12, %13, %14, %15, %16, %17, %18, %19, %20, %21, %22, %23, %24, %25, %26, %27, %28, %29, %30, %31, %32, %33, %34, %35, %36, %37, %38, %39, %40, %41, %42, %43, %44, %45, %46, %47, %48, %49, %50, %51, %52, %53, %54, %55, %56, %57, %58, %59, %60, %61, %62, %63, %64, %65, %66, %67, %68, %69, %70, %71}, dA, dB, pt, 1, 1, 0, 1;\n"
        "add.u32 t0, da, 4; add.u32 t1, db, 576; mov.b64 dA, {t0, hi}; mov.b64 dB, {t1, hb};\n"
        "wgmma.mma_async.sync.aligned.m64n144k16.f32.bf16.bf16 {%0, %1, %2, %3, %4, %5, %6, %7, %8, %9, %10, %11, %12, %13, %14, %15, %16, %17, %18, %19, %20, %21, %22, %23, %24, %25, %26, %27, %28, %29, %30, %31, %32, %33, %34, %35, %36, %37, %38, %39, %40, %41, %42, %43, %44, %45, %46, %47, %48, %49, %50, %51, %52, %53, %54, %55, %56, %57, %58, %59, %60, %61, %62, %63, %64, %65, %66, %67, %68, %69, %70, %71}, dA, dB, pt, 1, 1, 0, 1;\n"
        "add.u32 t0, da, 6; add.u32 t1, db, 864; mov.b64 dA, {t0, hi}; mov.b64 dB, {t1, hb};\n"
        "wgmma.mma_async.sync.aligned.m64n144k16.f32.bf16.bf16 {%0, %1, %2, %3, %4, %5, %6, %7, %8, %9, %10, %11, %12, %13, %14, %15, %16, %17, %18, %19, %20, %21, %22, %23, %24, %25, %26, %27, %28, %29, %30, %31, %32, %33, %34, %35, %36, %37, %38, %39, %40, %41, %42, %43, %44, %45, %46, %47, %48, %49, %50, %51, %52, %53, %54, %55, %56, %57, %58, %59, %60, %61, %62, %63, %64, %65, %66, %67, %68, %69, %70, %71}, dA, dB, pt, 1, 1, 0, 1;\n"
        "wgmma.commit_group.sync.aligned;\n"
        "setp.eq.u32 pa, k, k;\n"
        "mov.u32 cb, eb; add.u32 da, da, 512; add.u32 db, db, 1152; add.u32 eb, eb, %77;\n"
        "setp.eq.u32 pk, da, dwe; @pk mov.u32 da, %80; and.pred pk, pk, pw; @pk mov.u32 eb, %78;\n"
        "and.b32 eb, eb, em; setp.eq.u32 pk, dbe, db; @pk mov.u32 db, %85;\n"
        "wgmma.wait_group.sync.aligned 1;\n"
        "@pe mbarrier.arrive.shared::cluster.b64 _, [pb], %79;\n"
        "mov.u32 pb, cb; and.pred pr, p0, p1;\n"
        "add.u32 t0, wb, 64; setp.le.or.u32 pk, t0, we, pw; setp.ne.and.u32 pe, %79, 0, pk;\n"
        "setp.ne.u32 pk, wb, we; @pk bra.uni LOOP;\n"
        "wgmma.wait_group.sync.aligned 0;\n"
        "@pe mbarrier.arrive.shared::cluster.b64 _, [pb], %79;\n"
        "}\n"
        :
          "+f"(d[0]), "+f"(d[1]), "+f"(d[2]), "+f"(d[3]), "+f"(d[4]), "+f"(d[5]), "+f"(d[6]), "+f"(d[7]),
          "+f"(d[8]), "+f"(d[9]), "+f"(d[10]), "+f"(d[11]), "+f"(d[12]), "+f"(d[13]), "+f"(d[14]), "+f"(d[15]),
          "+f"(d[16]), "+f"(d[17]), "+f"(d[18]), "+f"(d[19]), "+f"(d[20]), "+f"(d[21]), "+f"(d[22]), "+f"(d[23]),
          "+f"(d[24]), "+f"(d[25]), "+f"(d[26]), "+f"(d[27]), "+f"(d[28]), "+f"(d[29]), "+f"(d[30]), "+f"(d[31]),
          "+f"(d[32]), "+f"(d[33]), "+f"(d[34]), "+f"(d[35]), "+f"(d[36]), "+f"(d[37]), "+f"(d[38]), "+f"(d[39]),
          "+f"(d[40]), "+f"(d[41]), "+f"(d[42]), "+f"(d[43]), "+f"(d[44]), "+f"(d[45]), "+f"(d[46]), "+f"(d[47]),
          "+f"(d[48]), "+f"(d[49]), "+f"(d[50]), "+f"(d[51]), "+f"(d[52]), "+f"(d[53]), "+f"(d[54]), "+f"(d[55]),
          "+f"(d[56]), "+f"(d[57]), "+f"(d[58]), "+f"(d[59]), "+f"(d[60]), "+f"(d[61]), "+f"(d[62]), "+f"(d[63]),
          "+f"(d[64]), "+f"(d[65]), "+f"(d[66]), "+f"(d[67]), "+f"(d[68]), "+f"(d[69]), "+f"(d[70]), "+f"(d[71])
        : "r"(wb), "r"(ab), "r"(da), "r"(db), "r"(eb), "r"(es), "r"(e0), "r"(cnt), "r"(dw0), "r"(acc), "r"(w0), "r"(ord), "r"(nch), "r"(db0), "r"(pre)
        : "memory");
}


__device__ __forceinline__ bool elect_one() {
    uint32_t p;
    asm volatile("{.reg .pred p; elect.sync _|p, 0xFFFFFFFF; selp.u32 %0, 1, 0, p;}" : "=r"(p));
    return p != 0;
}
template <int MODE>
__device__ __forceinline__ void mma_pass(float (&acc)[72], uint32_t sb, int warp, int lane, bool full, int accum, int wc, int ac, int nch,
                                         uint32_t boff, uint32_t wrel, uint32_t arel, int ord, int pre) {
    __syncwarp();
    sb = __shfl_sync(0xFFFFFFFFu, sb + lane, 0);
    const uint32_t bar = sb + SM_BAR;
    const uint32_t wb = bar + (B_WFULL + wc) * 8, ab = bar + (B_AFULL + ac) * 8;
    const uint32_t dw0 = (((sb + SM_W) & 0x3FFFF) >> 4) | 0x10000u;
    const uint32_t db0 = ((((sb + SM_ACT) & 0x3FFFF) + boff) >> 4) | (MODE == 2 ? 0x900000u : 0x10000u);
    const int ws = wc % WSLOTS, as = (MODE == 2) ? ac & 4 : 0;
    const uint32_t da = dw0 + ws * (WCH / 16), db = db0 + as * (SLOT / 16);
    const uint32_t e0 = (warp & 1) ? mapa(bar + B_AEMPTY * 8, 0) : bar + B_WEMPTY * 8;
    const uint32_t es = (warp & 1) ? mapa(bar + B_AEMPTY * 8, 1) - e0 : 8;
    const uint32_t eb = e0 + ((warp & 1) ? as : ws) * es;
    const uint32_t cnt = lane ? 0 : (warp == 0) ? wrel : (warp == 1) ? arel : 0;
    if (MODE == 0) kloop_s(acc, wb, ab, da, db, eb, es, e0, cnt, dw0, accum, warp == 0, ord, nch, db0, pre);
    else if (MODE == 2) kloop_c(acc, wb, ab, da, db, eb, es, e0, cnt, dw0, accum, warp == 0, ord, nch, db0, pre);
    else if (full) kloop_f(acc, wb, ab, da, db, eb, es, e0, cnt, dw0, accum, warp == 0, ord, nch, db0, pre);
    else
        kloop_h(acc, wb, ab, da, db, eb + (warp >> 1) * es, 2 * es, e0 + (warp >> 1) * es, lane ? 0 : (warp & 1) ? arel : wrel, dw0, accum, !(warp & 1), ord,
                nch, db0, pre);
}

__device__ __forceinline__ uint32_t img_addr(uint32_t base, int n, int g) { return base + n * 128 + ((g ^ (n & 7)) << 4); }

__device__ __forceinline__ void staged(uint32_t bar, uint32_t w) {
    fence_async();
    __syncwarp();
    if (elect_one()) mbar_arrive(bar, w);
}
__device__ __forceinline__ float tie(float v, float on) { return __uint_as_float(__float_as_uint(v) | (__float_as_uint(on) & blockIdx.y)); }
template <int O>
__device__ __forceinline__ void stage9(const float (&a)[72], uint32_t ad, uint32_t sp, bool out0, bool out1) {
#pragma unroll
    for (int j = 0; j < 9; j += 2) {
        uint32_t p[4];
#pragma unroll
        for (int i = 0; i < ((j < 8) ? 4 : 2); i++) {
            p[i] = pack2(gelu_h(a[O + 4 * j + 2 * i]), gelu_h(a[O + 4 * j + 2 * i + 1]));
        }
        if (j < 8) stsm4t((j == 0 && out0) ? sp : ad + j * 1024, p[0], p[1], p[2], p[3]);
        else stsm2t(out1 ? sp : ad + j * 1024, p[0], p[1]);
    }
}
__device__ __forceinline__ uint32_t pack_so(float sc, float of) {
    const uint32_t lo = pack2(of, 0.f) & 0xFFFFu;
    return ((__float_as_uint(sc) + 0x8000u - lo) & 0xFFFF0000u) | lo;
}
__device__ __forceinline__ int so_index(int n) { return (n & ~15) + 2 * (n & 6) + ((n >> 2) & 2) + (n & 1); }
__device__ __forceinline__ void hmma(float (&c)[4], const uint32_t (&a)[4], uint32_t b0, uint32_t b1) {
    asm volatile("mma.sync.aligned.m16n8k16.row.col.f32.bf16.bf16.f32 {%0, %1, %2, %3}, {%4, %5, %6, %7}, {%8, %9}, {%0, %1, %2, %3};"
                 : "+f"(c[0]), "+f"(c[1]), "+f"(c[2]), "+f"(c[3]) : "r"(a[0]), "r"(a[1]), "r"(a[2]), "r"(a[3]), "r"(b0), "r"(b1));
}
__device__ __forceinline__ void ln_fold(float (&acc)[72], uint32_t tab, float cs0, float cs1, bool half) {
    constexpr int NC = 36;
    uint32_t so[36];
#pragma unroll
    for (int i = 0; i < (NC + 3) / 4; i++)
        asm volatile("ld.shared.v4.u32 {%0, %1, %2, %3}, [%4];" : "=r"(so[4 * i]), "=r"(so[4 * i + 1]), "=r"(so[4 * i + 2]), "=r"(so[4 * i + 3]) : "r"(tab + 64 * i) : "memory");
#pragma unroll
    for (int c = 0; c < NC; c++) {
        if (c == 18 && half) break;
        const int e = 4 * (c >> 1) + (c & 1);
        if (c >= 18 && c % 2 == 0) { const float pv = acc[4 * ((c - 1) >> 1) + ((c - 1) & 1)]; cs0 = tie(cs0, pv); cs1 = tie(cs1, pv); }
        const float sc = __uint_as_float(so[c]), of = bf_lo(so[c]);
        acc[e] = fmaf(-of, cs0, acc[e]) * sc;
        acc[e + 2] = fmaf(-of, cs1, acc[e + 2]) * sc;
    }
}
__device__ __forceinline__ float2 cmul(float2 a, float2 b) { return make_float2(a.x * b.x - a.y * b.y, a.x * b.y + a.y * b.x); }
__device__ __forceinline__ float2 cfma(float2 a, float2 b, float2 c) {
    return make_float2(fmaf(a.x, b.x, fmaf(-a.y, b.y, c.x)), fmaf(a.x, b.y, fmaf(a.y, b.x, c.y)));
}
__device__ __forceinline__ float2 shfl2_up(float2 v, int d) {
    return make_float2(__shfl_up_sync(0xFFFFFFFFu, v.x, d), __shfl_up_sync(0xFFFFFFFFu, v.y, d));
}
__device__ __forceinline__ void cluster_wait() { asm volatile("barrier.cluster.wait.acquire.aligned;" ::: "memory"); }
__device__ __forceinline__ float rsq(float x) {
    float y;
    asm("rsqrt.approx.ftz.f32 %0, %1;" : "=f"(y) : "f"(x));
    return y;
}

__device__ __forceinline__ float bf_round(float x) { return bf_lo(pack2(x, 0.f)); }
__device__ __forceinline__ float ln_rstd(float var) {
    const float v = bf_round(bf_round(var) + LN_EPS);
    float y;
    asm("rcp.approx.ftz.f32 %0, %1;" : "=f"(y) : "f"(bf_round(v * rsq(v))));
    return y;
}

__global__ void __cluster_dims__(CL, 1, 1) __launch_bounds__(512, 1) fused_kernel(const __grid_constant__ Params P) {
    const uint32_t sb = smem_u32(smem);
    const uint32_t bar = sb + SM_BAR;
    const int tid = threadIdx.x, lane = tid & 31;
    const int wid = __shfl_sync(0xFFFFFFFFu, tid >> 5, 0), wg = wid >> 2, warp = wid & 3;
    const int r = blockIdx.x & (CL - 1), blk = blockIdx.x >> 3;
    const int T0 = blk * BLK - 2;

    const bool statw = (wid >= 4 && wid < 12) || wid == 14;
    const int srow = (wid == 14) ? 16 + (lane >> 4) : (tid - 128) >> 4;
    uint4 xv[4];
    if (statw) {
        const int t = T0 + 18 * r + srow;
        const uint4* p = reinterpret_cast<const uint4*>(P.xp) + (t * (DM / 8) + (tid & 15));
#pragma unroll
        for (int i = 0; i < 4; i++) xv[i] = ((unsigned)t < (unsigned)L_SEQ) ? __ldg(p + 16 * i) : make_uint4(0, 0, 0, 0);
    }
    unsigned short chp[4];
    unsigned epo = 0;
    if (wid == 12) {
        if (elect_one()) {
#pragma unroll
            for (int i = 0; i < WSLOTS; i++) mbar_init(bar + (B_WFULL + i) * 8, 1);
#pragma unroll 1
            for (int i = 0; i < WSLOTS; i++) {
                mbar_expect(bar + (B_WFULL + i) * 8, WCH);
                tma2d(sb + SM_W + i * WCH, &P.w[0], 64 * r, 64 * i, bar + (B_WFULL + i) * 8);
            }
#pragma unroll
            for (int i = WSLOTS; i < 8; i++)
                asm volatile("cp.async.bulk.prefetch.tensor.2d.L2.global [%0, {%1, %2}];" ::"l"(&P.w[0]), "r"(64 * r), "r"(64 * i) : "memory");
        }
        __syncwarp();
    } else if (wid == 13) {
        if (elect_one()) {
#pragma unroll
            for (int i = 0; i < 8; i++) mbar_init(bar + (B_AFULL + i) * 8, 1);
#pragma unroll 1
            for (int i = 0; i < 8; i++) {
                mbar_expect(bar + (B_AFULL + i) * 8, CPB);
                tma2d(sb + SM_ACT + i * SLOT, &P.x, 64 * i, T0, bar + (B_AFULL + i) * 8);
            }
        }
        __syncwarp();
    } else if (wid == 15) {
        if (elect_one()) {
            mbar_init(bar + B_ST1 * 8, 1);
            mbar_init(bar + B_AEMPTY * 8, CL * 4);
            mbar_init(bar + B_XP * 8, CL);
            mbar_expect(bar + B_ST1 * 8, NT * 16);
        }
        __syncwarp();
        asm volatile("fence.mbarrier_init.release.cluster;" ::: "memory");
    }
    asm volatile("barrier.cluster.arrive.relaxed.aligned;" ::: "memory");
    if (wid < 4) {
        const int iw = wid, it = tid;
        if (elect_one()) {
            const int b0 = (0xA2743806u >> (8 * iw)) & 255;
#pragma unroll
            for (int i = 0; i < 52; i++) mbar_init(bar + (b0 + i) * 8, 1);
        }
        __syncwarp();
        const uint32_t v = (it & 8) ? 0x3F803F80u : 0u;
        *reinterpret_cast<uint4*>(smem + SM_ACT + (it >> 4) * SLOT + CPB + (it & 15) * 16) = make_uint4(v, v, v, v);
        fence_async();
        bar_sync(8, 128);
        if (it < 102) mbar_expect(bar + (WSLOTS + it) * 8, WCH);
        const uint32_t h1 = (r & 1) ? CPB - HALFB : HALFB;
        if (it < 78 && it != 16 + r && it != 70 + r)
            mbar_expect(bar + (B_AFULL + 8 + it) * 8, it >= 70 ? h1 : (unsigned)(it - 16) < 8u ? CPB - h1 : (unsigned)(it - 52) < 16u ? SLOT : CPB);
    } else if (wid == 15) {
        if (elect_one()) {
#pragma unroll
            for (int i = B_WEMPTY; i < B_XP; i++) mbar_init(bar + i * 8, i < B_SAF ? 2 : 8);
            mbar_init(bar + B_G * 8, 4);
            mbar_init(bar + B_ST3 * 8, 1);
            mbar_expect(bar + B_ST3 * 8, HALFB);
#pragma unroll 1
            for (int i = 8; i > 0; i--) asm volatile("prefetch.tensormap [%0];" ::"l"(&P.w[i]) : "memory");
        }
    }
    __syncwarp();
    if (statw) {
        const uint32_t* w = reinterpret_cast<const uint32_t*>(xv);
        float d[32], s = 0.f;
#pragma unroll
        for (int k = 0; k < 16; k++) { d[2 * k] = bf_lo(w[k]); d[2 * k + 1] = bf_hi(w[k]); s += d[2 * k] + d[2 * k + 1]; }
#pragma unroll
        for (int o = 8; o; o >>= 1) s += __shfl_xor_sync(0xFFFFFFFFu, s, o);
        const float mean = s * (1.0f / DM);
        float ss = 0.f, st = 0.f;
#pragma unroll
        for (int k = 0; k < 16; k++) {
            d[2 * k] -= mean; d[2 * k + 1] -= mean;
            ss = fmaf(d[2 * k], d[2 * k], ss); st = fmaf(d[2 * k + 1], d[2 * k + 1], st);
        }
        ss += st;
#pragma unroll
        for (int o = 8; o; o >>= 1) ss += __shfl_xor_sync(0xFFFFFFFFu, ss, o);
        const float var = ss * (1.0f / DM);
        const float r1 = ln_rstd(var), mb = bf_round(mean), dm = (mean - mb) * r1;
        unsigned char* dst = smem + SM_STGA + (((tid >> 3) & 1) * 18 + srow) * 128 + (((tid & 7) ^ ((r & 6) + (srow & 1))) << 4);
#pragma unroll
        for (int i = 0; i < 4; i++)
            *reinterpret_cast<uint4*>(dst + i * (2 * 18 * 128)) =
                make_uint4(pack2(fmaf(d[8 * i], r1, dm), fmaf(d[8 * i + 1], r1, dm)), pack2(fmaf(d[8 * i + 2], r1, dm), fmaf(d[8 * i + 3], r1, dm)),
                           pack2(fmaf(d[8 * i + 4], r1, dm), fmaf(d[8 * i + 5], r1, dm)), pack2(fmaf(d[8 * i + 6], r1, dm), fmaf(d[8 * i + 7], r1, dm)));
        fence_async();
        asm volatile("bar.arrive 10, 320;" ::: "memory");
        if (wg == 2) {
            const int p = 64 * r + (tid & 63);
            chp[0] = __ldg(reinterpret_cast<const unsigned short*>(P.lre) + p); chp[1] = __ldg(reinterpret_cast<const unsigned short*>(P.lim) + p);
            chp[2] = __ldg(reinterpret_cast<const unsigned short*>(P.ldt) + p); chp[3] = __ldg(reinterpret_cast<const unsigned short*>(P.dsk) + p);
            epo = g_epoch[blockIdx.x] + 1;
        }
        const float r2 = ln_rstd(var * r1 * r1);
        const int tau = 18 * r + srow;
        cluster_wait();
        st_async2(mapa(sb + ((lane & 8) ? SM_TABB : SM_TABA) + tau * 8, lane & 7), (lane & 8) ? mb : mean, (lane & 8) ? r1 : 0.5f * r1 * r2,
                  mapa(bar + B_ST1 * 8, lane & 7));
    }
    if (!statw) { bar_sync(11, 224); asm volatile("bar.arrive 12, 512;" ::: "memory"); }
    else bar_sync(12, 512);

    if (wg == 3) {
        asm volatile("setmaxnreg.dec.sync.aligned.u32 24;");
        unsigned char* img = g_img + (size_t)blockIdx.x * (NIMG * SLOT);
        if (warp == 0) {
            const int tb = 7 * (r >> 1) + 3 * (r & 1);
            int ph = 0;
            uint32_t fb = bar + (B_WFULL + WSLOTS) * 8, eb = bar + B_WEMPTY * 8, dst = sb + SM_W;
#pragma unroll 1
            for (int g = 0; g < 14; g++) {
                int mi = (g & 2) ? g ^ 1 : g, c0 = 64 * r, m2 = 128, m1 = 64, cb = 0;
                if (g >= 8) { mi = 6; m2 = 448; m1 = 192; cb = 64 * (g - 9); }
                else if (g >= 4) { mi = 4; c0 = 64 * ((g == 4) ? 7 * (r >> 1) + 6 : tb + g - 5); }
                if (g == 8) { m2 = 896; m1 = 448; cb = 384; }
                if (g >= 12) { mi = 2 * g - 19; m2 = 128; m1 = 64; cb = 0; }
                const CUtensorMap* m = &P.w[mi];
                const bool sw = mi & 1;
#pragma unroll 1
                for (int k = g ? 0 : WSLOTS; k < ((g == 8) ? 4 : 8); k += 2) {
                    const int c1 = cb + m2 * (((g > 8) ? k ^ 4 : k) >> 1);
#pragma unroll
                    for (int e = 0; e < 2; e++) wait_tma2d(eb + e * 8, ph, dst + e * WCH, m, sw ? c1 + e * m1 : c0, sw ? c0 : c1 + e * m1, fb + e * 8);
                    fb += 16; eb += 16; dst += 2 * WCH;
                    if (dst == sb + SM_W + WSLOTS * WCH) { dst = sb + SM_W; eb = bar + B_WEMPTY * 8; ph ^= 1; }
                }
            }
        } else if (warp == 1) {
            cluster_wait();
            bar_sync(10, 320);
            asm volatile("bar.arrive 3, 160;" ::: "memory");
            if (elect_one()) {
                asm volatile("cp.async.bulk.tensor.3d.global.shared::cta.bulk_group [%0, {%2, %3, %4}], [%1];"
                             ::"l"(&P.xn), "r"(sb + SM_STGA), "r"(128 * (r >> 1)), "r"(9 * (r & 1)), "r"(blk * CL) : "memory");
                asm volatile("cp.async.bulk.commit_group;" ::: "memory");
                asm volatile("cp.async.bulk.wait_group 0;" ::: "memory");
            }
            __syncwarp();
            if (lane < 8) asm volatile("mbarrier.arrive.shared::cluster.b64 _, [%0];" ::"r"(mapa(bar + B_XP * 8, lane)) : "memory");
            __syncwarp();
            int ph = 0;
#pragma unroll 1
            for (int rd = 1; rd < 10; rd++) {
                if (rd == 4 && r >= 4) continue;
                const uint32_t fb = bar + (B_AFULL + rd * 8 + (rd > 4 ? (r ^ 4) - 4 : r)) * 8;
                const int item = (rd == 1) ? 8 : rd - 2;
                if (rd != 3) mbar_wait_cluster(bar + (rd == 1 ? B_XP : rd == 4 ? B_STD : B_STORED + min(item, 6)) * 8);
                if (rd <= 2) {
                    const unsigned c0 = clock();
                    while ((unsigned)clock() - c0 < (unsigned)(r * STAGGER)) {}
                }
                if (rd == 1) mbar_wait(bar + B_XR * 8, 0);
                if (rd == 3) mbar_wait(bar + B_AEMPTY * 8, ph);
                else wait_bulk_mc(bar + B_AEMPTY * 8, ph, sb + SM_ACT + r * SLOT, img + item * SLOT, (rd >= 8) ? SLOT : CPB, fb);
                ph ^= 1;
            }
            return;
        } else if (warp == 2) {
#pragma unroll 1
            for (int u = 0; u < 9; u++) {
                const int item = (0x554433210ull >> (4 * u)) & 15;
                const int up = (u == 2) ? (r & 1) : (0x150 >> u) & 1;
                const int own = (u == 2) ? r >> 1 : r;
                mbar_wait(bar + (B_SAF + u) * 8, 0);
                if (u == 1) {
                    if (elect_one()) {
                        bulk_store(img + SLOT, sb + SM_ACT + r * SLOT, CPB);
                        asm volatile("cp.async.bulk.commit_group;" ::: "memory");
                        mbar_arrive(bar + (B_AFULL + 24 + r) * 8, 1);
                        mbar_arrive(bar + (B_AH + r) * 8, 1);
                    }
                    mbar_wait(bar + B_AEMPTY * 8, 0);
                    if (elect_one()) {
                        asm volatile("cp.async.bulk.wait_group 0;" ::: "memory");
                        const unsigned c0 = clock();
#pragma unroll 1
                        for (int ps = 0; ps < 2; ps++) {
                            while ((unsigned)clock() - c0 < (unsigned)((r + 8 * ps) * (STAGGER / 2))) {}
                            const uint32_t fb = bar + (ps ? B_AFULL + 24 + r : B_AH + r) * 8, me = 0xFFu ^ (1u << r);
                            bulk_mc(sb + SM_ACT + r * SLOT, img + SLOT, HALFB, fb, (uint16_t)((ps ? 0xAAu : 0x55u) & me));
                            bulk_mc(sb + SM_ACT + r * SLOT + HALFB, img + SLOT + HALFB, CPB - HALFB, fb, (uint16_t)((ps ? 0x55u : 0xAAu) & me));
                        }
                    }
                    __syncwarp();
                } else if (elect_one()) {
                    bulk_store(img + ((own - r) * NIMG + item) * SLOT + up * HALFB, sb + ((u == 2) ? SM_STGB : SM_STGA + up * HALFB), (u < 2) ? CPB : HALFB);
                    asm volatile("cp.async.bulk.commit_group;" ::: "memory");
                    asm volatile("cp.async.bulk.wait_group.read 0;" ::: "memory");
                    mbar_arrive(bar + (B_SAE + u) * 8, 1);
                    if (u == 8) tma2d(sb + SM_STGA, &P.x, 64 * r, T0, bar + B_XF * 8);
                    if ((0x157 >> u) & 1) {
                        asm volatile("cp.async.bulk.wait_group 0;" ::: "memory");
                        asm volatile("mbarrier.arrive.shared::cluster.b64 _, [%0];" ::"r"(mapa(bar + ((u == 2) ? B_STD : B_STORED + item) * 8, own)) : "memory");
                    }
                }
                __syncwarp();
            }
            mbar_wait(bar + B_XE * 8, 0);
            if (elect_one())
                asm volatile("cp.async.bulk.shared::cluster.global.mbarrier::complete_tx::bytes [%0], [%1], %2, [%3];"
                             ::"r"(sb + SM_STGA), "l"(img + SLOT), "r"(CPB), "r"(bar + B_X1 * 8) : "memory");
            return;
        } else {
#pragma unroll 1
            for (int i = 1; i < 8; i++) {
                if (i == 1) mbar_wait(bar + (B_AFULL + 7) * 8, 0);
                if (i == 4) mbar_wait(bar + (B_WFULL + PF_AFTER) * 8, 0);
                const uint32_t piece = (i & 6) == 4 ? (uint32_t)(DM * FF * 2 / 112) : (uint32_t)(DM * DM * 2 / 64);
                if (blockIdx.x < ((i & 6) == 4 ? 112 : 64) && elect_one())
                    asm volatile("cp.async.bulk.prefetch.L2.global [%0], %1;" ::"l"(P.pf[i] + blockIdx.x * piece), "r"(piece) : "memory");
            }
#pragma unroll 1
            for (int u = 0; u < 2; u++) {
                mbar_wait(bar + (B_SBF + u) * 8, 0);
                if (elect_one()) {
                    bulk_store(img + (6 + u) * SLOT, sb + SM_STGA, SLOT);
                    asm volatile("cp.async.bulk.commit_group;" ::: "memory");
                    asm volatile("cp.async.bulk.wait_group.read 0;" ::: "memory");
                    mbar_arrive(bar + (u ? B_SAE + 1 : B_SBE) * 8, 1);
                    if (u) {
                        asm volatile("cp.async.bulk.wait_group 0;" ::: "memory");
                        mbar_arrive(bar + (B_STORED + 6) * 8, 1);
                    }
                }
                __syncwarp();
            }
        }
        cluster_wait();
    } else {
        if (wid < 4) cluster_wait();
        const int q = lane & 3, tl = tid & 127;
        const int gq = 2 * warp + ((lane >> 3) & 1), lrow = (lane >> 4) * 8 + (lane & 7);
        if (wg == 2) {
            asm volatile("setmaxnreg.inc.sync.aligned.u32 232;");
            float aR[72], aI[72];
            if (tl < 64) {
                const float lr = bf_lo(chp[0]), li = bf_lo(chp[1]), dt = bf_round(expf(bf_lo(chp[2])));
                *reinterpret_cast<float*>(smem + SM_DSK + tl * 4) = bf_lo(chp[3]);
                float sn, cs;
                sincospif(dt * li * 0.318309886183790672f, &sn, &cs);
                const float mag = expf(dt * lr);
                const float2 a = make_float2(mag * cs, mag * sn);
                const float den = __fdividef(2.0f, lr * lr + li * li);
                const float nr = a.x - 1.0f, ni = a.y;
                *reinterpret_cast<float4*>(smem + SM_CHA + tl * 16) =
                    make_float4(a.x, a.y, (nr * lr + ni * li) * den, (ni * lr - nr * li) * den);
                const float2 a2 = cmul(a, a), a4 = cmul(a2, a2), a8 = cmul(a4, a4), a16 = cmul(a8, a8), a32 = cmul(a16, a16),
                             a64 = cmul(a32, a32), a36 = cmul(a32, a4);
                static_assert(BLK == 128 + 8 + 2, "");
                *reinterpret_cast<float2*>(smem + SM_CHB + tl * 8) = cmul(cmul(a64, a64), cmul(a8, a2));
                *reinterpret_cast<float4*>(smem + SM_CHC + tl * 16) = make_float4(a36.x, a36.y, a32.x, a32.y);
            }
            bar_sync(7, 128);
            float2 a1[2], a36[2], a30[2], h[2];
#pragma unroll
            for (int i = 0; i < 2; i++) {
                const float4 ch = lds128(SM_CHC + (16 * warp + 8 * i + (lane >> 2)) * 16);
                a36[i] = make_float2(ch.x, ch.y);
                a30[i] = make_float2(ch.z, ch.w);
            }
            mma_pass<0>(aR, sb, warp, lane, false, 0, 8, 8, 8, 0, 2, 0, 0, 2);
            mma_pass<0>(aI, sb, warp, lane, false, 0, 16, 8, 8, 0, 2, 4, 0, 0);
            {
                const unsigned ep = epo;
#pragma unroll
                for (int i = 0; i < 2; i++) {
                    const float4 ch = lds128(SM_CHA + (16 * warp + 8 * i + (lane >> 2)) * 16);
                    a1[i] = make_float2(ch.x, ch.y);
                    float2 c2 = make_float2(ch.z, ch.w);
                    if (i) { c2.x = tie(c2.x, h[0].x); c2.y = tie(c2.y, h[0].x); }
                    const float2 a2 = cmul(a1[i], a1[i]);
                    float2 s = make_float2(0.f, 0.f), s32;
#pragma unroll
                    for (int j = 0; j < 18; j++) {
                        const int e0 = 4 * j + 2 * i;
                        c2.x = tie(c2.x, s.x); c2.y = tie(c2.y, s.x);
                        const float2 v0 = cmul(c2, make_float2(aR[e0], aI[e0])), v1 = cmul(c2, make_float2(aR[e0 + 1], aI[e0 + 1]));
                        aR[e0] = v0.x; aI[e0] = v0.y; aR[e0 + 1] = v1.x; aI[e0 + 1] = v1.y;
                        s = cfma(a2, s, cfma(a1[i], v0, v1));
                        if (j == 0 && q == 0) s = make_float2(0.f, 0.f);
                        if (j == 15) s32 = s;
                    }
                    const float2 a72 = cmul(a36[i], a36[i]);
                    float2 t = shfl2_up(s, 1);
                    if (q >= 1) s = cfma(a36[i], t, s);
                    t = shfl2_up(s, 2);
                    if (q >= 2) s = cfma(a72, t, s);
                    h[i] = shfl2_up(s, 1);
                    if (q == 0) h[i] = make_float2(0.f, 0.f);
                    const float2 e = cfma(a30[i], h[i], s32);
                    if (q == 3)
                        asm volatile("{.reg .b64 v; mov.b64 v, {%1, %2}; st.relaxed.gpu.global.b64 [%0], v;}"
                                     ::"l"(g_end + blk * DM + 64 * r + 16 * warp + 8 * i + (lane >> 2)),
                                       "r"((__float_as_uint(e.x) & ~1u) | (ep & 1u)), "r"((__float_as_uint(e.y) & ~1u) | (ep & 1u)) : "memory");
                    a30[i] = cmul(a30[i], a2);
                    if (q >= 2) a30[i] = cmul(a30[i], (q == 2) ? a36[i] : a72);
                    if (q == 0) a30[i] = make_float2(1.f, 0.f);
                }
                const int hf = tl >> 6, mid = blk >> 1, cnt = hf ? blk - mid : mid;
                const unsigned long long* src = g_end + (hf ? mid : 0) * DM + 64 * r + (tl & 63);
                const float2 A = lds64(SM_CHB + (tl & 63) * 8);
                float2 H;
                int tries = 1 << 14;
                unsigned bad;
                do {
                    if (tries != (1 << 14)) __nanosleep(200);
                    uint2 ev[7];
#pragma unroll
                    for (int k = 0; k < 7; k++)
                        asm volatile("{.reg .b64 v; .reg .pred p; setp.lt.s32 p, %3, %4; mov.b64 v, 0; @p ld.relaxed.gpu.global.b64 v, [%2]; mov.b64 {%0, %1}, v;}"
                                     : "=r"(ev[k].x), "=r"(ev[k].y) : "l"(src + k * DM), "r"(k), "r"(cnt) : "memory");
                    bad = 0;
                    H = make_float2(0.f, 0.f);
#pragma unroll
                    for (int k = 0; k < 7; k++) {
                        if (k < cnt) {
                            bad |= (ev[k].x ^ ep) | (ev[k].y ^ ep);
                            H = cfma(A, H, make_float2(__uint_as_float(ev[k].x), __uint_as_float(ev[k].y)));
                        }
                    }
                } while ((bad & 1u) && --tries);
#pragma unroll 1
                for (int k = hf ? blk : mid; k < blk; k++) H = cmul(A, H);
                *reinterpret_cast<float2*>(smem + SM_HP + tl * 8) = H;
                bar_sync(7, 128);
                if (tl == 0) g_epoch[blockIdx.x] = ep;
#pragma unroll
                for (int i = 0; i < 2; i++) {
                    const int ch = 16 * warp + 8 * i + (lane >> 2);
                    const float2 h0 = lds64(SM_HP + ch * 8), h1 = lds64(SM_HP + (64 + ch) * 8);
                    h[i] = cfma(a30[i], make_float2(h0.x + h1.x, h0.y + h1.y), h[i]);
                }
            }
            uint32_t oR[36], oI[36];
#pragma unroll
            for (int j = 0; j < 18; j++) {
#pragma unroll
                for (int i = 0; i < 2; i++) {
                    const int e0 = 4 * j + 2 * i;
                    const float2 hin = make_float2(tie(h[i].x, h[i ^ 1].x), h[i].y);
                    const float2 h0 = cfma(a1[i], hin, make_float2(aR[e0], aI[e0]));
                    h[i] = cfma(a1[i], h0, make_float2(aR[e0 + 1], aI[e0 + 1]));
                    if (j == 0 && q == 0) h[i] = hin;
                    oR[18 * i + j] = pack2(h0.x, h[i].x);
                    oI[18 * i + j] = pack2(-h0.y, -h[i].y);
                }
            }
#pragma unroll
            for (int i = 0; i < 36; i++) asm volatile("" : "+r"(oR[i]), "+r"(oI[i]));
#pragma unroll
            for (int u = 0; u < 2; u++) {
                mbar_wait(bar + (u ? B_SBE : B_SAE) * 8, 0);
                unsigned char* dst = smem + SM_STGA + warp * 4608 + (lane >> 2) * 16 + ((9 * q) >> 1) * 128;
                const uint32_t* o = u ? oI : oR;
#pragma unroll
                for (int jj = 0; jj < 18; jj++) {
                    const int c = jj % 9, off = (jj / 9) * 2304 + (c >> 1) * 128 + ((c & 1) ? ((q & 1) ? 128 : 8) : ((q & 1) ? 8 : 0));
                    *reinterpret_cast<uint2*>(dst + off) = make_uint2(o[2 * jj], o[2 * jj + 1]);
                }
                staged(bar + (B_SBF + u) * 8, 2);
            }
            asm volatile("setmaxnreg.dec.sync.aligned.u32 128;");
        }
        {
            float acc[72];
#pragma unroll 1
            for (int o = (wg == 2) ? 10 : wg; o < 10 + (wg >> 1); o += 2) {
                const int st = o >> 1;
                const bool half = o == 6;
                const int nb = half ? (r & 1) * NH : 0;
                if (o == 1) {
                    mbar_wait(bar + (B_AFULL + r) * 8, 0);
                    const uint32_t ad = img_addr(sb + SM_ACT + r * SLOT, lrow, gq);
                    uint32_t x[36];
#pragma unroll
                    for (int j = 0; j < 9; j++) ldsm4t(ad + j * 2048, x[4 * j], x[4 * j + 1], x[4 * j + 2], x[4 * j + 3]);
                    __threadfence_block();
                    __syncwarp();
                    if (elect_one()) mbar_arrive(bar + B_XR * 8, 2);
                    mbar_wait(bar + B_SAF * 8, 0);
#pragma unroll
                    for (int i = 0; i < 36; i++) { asm volatile("" : "+r"(x[i])); acc[2 * i] = bf_lo(x[i]); acc[2 * i + 1] = bf_hi(x[i]); }
                }
                if (o == 0 || o == 3 || o >= 6) {
                    mma_pass<1>(acc, sb, warp, lane, !half, o == 3, (o < 6) ? 24 * wg : (o > 8) ? 136 - 8 * o : 8 * o - 16, (o < 6) ? 16 * wg : (o == 9) ? 32 : half ? B_AH - B_AFULL : 24,
                                (o == 9) ? 28 : 8, nb * 128, 2, (o < 6 || o == 9) ? 4 : (o == 6) ? 0 : (o == 10) ? 2 : 1, (o >= 6 && o < 9) ? o - 2 : o ? 0 : 2,
                                (o == 7 || o == 8) ? o - 3 : (o == 10) ? 6 : o ? 0 : 3);
                    if (o == 9) break;
                }
                if (o == 2) continue;
                if (st == 2) {
                    bar_sync(8, 256);
#pragma unroll 1
                    for (int tg = wid ^ 4; tg < 9; tg += 8) {
                        float c0[4] = {0.f, 0.f, 0.f, 0.f}, c1[4] = {0.f, 0.f, 0.f, 0.f}, c2[4] = {0.f, 0.f, 0.f, 0.f};
                        const int row = 16 * tg + (lane & 15);
#pragma unroll
                        for (int k = 0; k < 4; k++) {
                            uint32_t f[4];
                            asm volatile("ldmatrix.sync.aligned.m8n8.x4.shared.b16 {%0, %1, %2, %3}, [%4];"
                                         : "=r"(f[0]), "=r"(f[1]), "=r"(f[2]), "=r"(f[3]) : "r"(img_addr(sb + SM_ACT + r * SLOT, row, 2 * k + (lane >> 4))) : "memory");
                            hmma(c0, f, f[0], f[2]);
                            hmma(c1, f, f[1], f[3]);
                            hmma(c2, f, 0x3F803F80u, 0x3F803F80u);
                        }
                        const int g = lane >> 2, pp = lane & 7, s0 = 8 * (pp & 3) + (pp & 3);
                        const float dl = (g & 1) ? c0[1] : c0[0], dh = (g & 1) ? c1[3] : c1[2];
                        float v[8];
#pragma unroll
                        for (int i = 0; i < 2; i++) {
                            v[4 * i] = __shfl_sync(0xFFFFFFFFu, c2[0], s0 + 4 * i); v[4 * i + 1] = __shfl_sync(0xFFFFFFFFu, dl, s0 + 4 * i);
                            v[4 * i + 2] = __shfl_sync(0xFFFFFFFFu, c2[2], s0 + 4 * i); v[4 * i + 3] = __shfl_sync(0xFFFFFFFFu, dh, s0 + 4 * i);
                        }
                        const bool up = pp >= 4;
#pragma unroll
                        for (int d = 0; d < 2; d++)
                            asm volatile("{.reg .pred p; setp.ne.u32 p, %6, 0;\n"
                                         "@p st.async.weak.shared::cluster.mbarrier::complete_tx::bytes.v4.f32 [%0], {%1, %2, %3, %4}, [%5];}"
                                         ::"r"(mapa(sb + SM_STGB + r * (NT * 8) + tg * 128 + ((pp ^ r) << 4), 2 * (lane >> 3) + d)),
                                           "f"(up ? v[2] : v[0]), "f"(up ? v[3] : v[1]), "f"(up ? v[6] : v[4]), "f"(up ? v[7] : v[5]),
                                           "r"(mapa(bar + B_ST3 * 8, 2 * (lane >> 3) + d)), "r"(1u) : "memory");
                    }
                    if (!wg) continue;
                    mbar_wait(bar + B_ST3 * 8, 0);
#pragma unroll 1
                    for (int m = tl; m < NT; m += 128) {
                        float s0 = 0.f, s1 = 0.f;
#pragma unroll
                        for (int i = 0; i < CL; i++) {
                            const float2 v = lds64(SM_STGB + i * (NT * 8) + ((m ^ (i << 1)) << 3));
                            s0 += v.x; s1 += v.y;
                        }
                        const float mu = s0 * (1.0f / DM), rh = 0.5f * ln_rstd(fmaxf(fmaf(-mu, mu, s1 * (1.0f / DM)), 0.f));
                        const uint32_t w = pack_so(rh, mu);
                        *reinterpret_cast<uint32_t*>(smem + SM_TABA + so_index(m) * 4) = w;
                        if (m >= NH) *reinterpret_cast<uint32_t*>(smem + SM_TABA + NT * 4 + so_index(m - NH) * 4) = w;
                    }
                    __syncwarp();
                    if (elect_one()) mbar_arrive(bar + B_TAB * 8, 2);
                    continue;
                }
                int n = nb + lrow;
                if (st != 1) {
                    const bool c0 = half && !nb;
                    float cs0 = __shfl_sync(0xFFFFFFFFu, half ? (c0 ? acc[0] : acc[33]) : acc[69], c0 ? lane & ~3 : lane | 3);
                    float cs1 = __shfl_sync(0xFFFFFFFFu, half ? (c0 ? acc[2] : acc[35]) : acc[71], c0 ? lane & ~3 : lane | 3);
                    if (o == 1) cs0 = cs1 = 1.0f;
                    if (o == 0) n += (r & 2) ? -1 - (r >> 2) : 1 + (r >> 2);
                    mbar_wait(bar + (st ? B_TAB : o ? B_SAF : B_ST1) * 8, 0);
                    if (st) {
                        ln_fold(acc, sb + SM_TABA + (nb ? NT * 4 : 0) + 16 * q, cs0, cs1, half);
                    } else {
#pragma unroll
                        for (int j = 0; j < 18; j++) {
                            const float4 sv = lds128((o ? SM_TABB : SM_TABA) + 16 * q + 64 * j);
                            if (j && j % 2 == 0) { cs0 = tie(cs0, acc[4 * j - 1]); cs1 = tie(cs1, acc[4 * j - 1]); }
                            acc[4 * j] = fmaf(-sv.x, cs0, acc[4 * j]) * sv.y;
                            acc[4 * j + 1] = fmaf(-sv.z, cs0, acc[4 * j + 1]) * sv.w;
                            acc[4 * j + 2] = fmaf(-sv.x, cs1, acc[4 * j + 2]) * sv.y;
                            acc[4 * j + 3] = fmaf(-sv.z, cs1, acc[4 * j + 3]) * sv.w;
                        }
                    }
                }
                if (o == 1) continue;
                const int u = (o == 10) ? 7 : (o > 6) ? 2 * o - 11 : (o + 1) / 3;
                const uint32_t ad = img_addr(sb + ((st == 1) ? SM_ACT + r * SLOT : half ? SM_STGB - nb * 128 : SM_STGA), n, gq), sp = sb + SM_STGA + (NT - 1) * 128;
                if (st == 1) bar_sync(9, 128);
                else if (!half) mbar_wait(bar + (u ? B_SAE + u - 2 : B_XP) * 8, 0);
                if (st == 1) {
                    if (q == 0) acc[0] = acc[2] = 1.0f;
                    if (q == 3) acc[69] = acc[71] = 1.0f;
#pragma unroll
                    for (int j = 0; j < 9; j++)
                        stsm4t(ad + j * 2048, pack2(acc[8 * j], acc[8 * j + 1]), pack2(acc[8 * j + 2], acc[8 * j + 3]),
                               pack2(acc[8 * j + 4], acc[8 * j + 5]), pack2(acc[8 * j + 6], acc[8 * j + 7]));
                } else {
                    stage9<0>(acc, ad, sp, n < 0, false);
                    if (!half) {
                        if (st) {
                            staged(bar + (B_SAF + u) * 8, 2);
                            mbar_wait(bar + (B_SAE + u - 1) * 8, 0);
                        }
                        stage9<36>(acc, ad + HALFB, sp, false, n + 136 >= NT);
                    }
                }
                staged(bar + (B_SAF + u + (o > 6)) * 8, 2);
            }
            if (wg == 1) {
                mbar_wait(bar + B_X1 * 8, 0);
#pragma unroll 1
                for (int hh = 0; hh < 2; hh++) {
                    const uint32_t ad = img_addr(sb + SM_STGA, lrow, gq) + hh * HALFB;
                    uint32_t p[18];
#pragma unroll
                    for (int j = 0; j < 8; j += 2) ldsm4t(ad + j * 1024, p[2 * j], p[2 * j + 1], p[2 * j + 2], p[2 * j + 3]);
                    asm volatile("ldmatrix.sync.aligned.m8n8.x2.trans.shared.b16 {%0, %1}, [%2];" : "=r"(p[16]), "=r"(p[17]) : "r"(ad + 8192) : "memory");
#pragma unroll
                    for (int i = 0; i < 18; i++) {
                        float gg[2];
#pragma unroll
                        for (int e = 0; e < 2; e++) {
                            const float b = (e ? bf_hi(p[i]) : bf_lo(p[i])) + acc[2 * i + e];
                            const float hb = 0.5f * b;
                            float th;
                            asm("tanh.approx.f32 %0, %1;" : "=f"(th) : "f"(hb));
                            gg[e] = fmaf(hb, th, hb);
                            acc[2 * i + e] = acc[36 + 2 * i + e];
                        }
                        p[i] = pack2(gg[0], gg[1]);
                    }
#pragma unroll
                    for (int j = 0; j < 8; j += 2) stsm4t(ad + j * 1024, p[2 * j], p[2 * j + 1], p[2 * j + 2], p[2 * j + 3]);
                    stsm2t(ad + 8192, p[16], p[17]);
                }
                __threadfence_block();
                __syncwarp();
                if (elect_one()) mbar_arrive(bar + B_G * 8, 1);
            }
        }
        if (wg == 2) {
            asm volatile("setmaxnreg.inc.sync.aligned.u32 168;");
            {
                const int nhi = min(BLK, L_SEQ - 2 - T0);
                float ay[72];
                uint32_t xs[36];
                {
                    mbar_wait(bar + B_XF * 8, 0);
#pragma unroll
                    for (int j = 0; j < 9; j++) ldsm4t(img_addr(sb + SM_STGA, lrow, gq) + j * 2048, xs[4 * j], xs[4 * j + 1], xs[4 * j + 2], xs[4 * j + 3]);
                    __threadfence_block();
                    __syncwarp();
                    if (elect_one()) mbar_arrive(bar + B_XE * 8, 2);
                    const float* dk = reinterpret_cast<const float*>(smem + SM_DSK) + 16 * warp + (lane >> 2);
                    const float dk0 = dk[0], dk1 = dk[8];
#pragma unroll
                    for (int j = 0; j < 18; j++) {
                        float4 st = lds128(SM_TABB + (8 * j + 2 * q) * 8);
                        if (j) { st.x = tie(st.x, ay[4 * j - 1]); st.z = tie(st.z, ay[4 * j - 1]); }
#pragma unroll
                        for (int i = 0; i < 2; i++) {
                            ay[4 * j + 2 * i] = (bf_lo(xs[2 * j + i]) - st.x) * st.y * (i ? dk1 : dk0);
                            ay[4 * j + 2 * i + 1] = (bf_hi(xs[2 * j + i]) - st.z) * st.w * (i ? dk1 : dk0);
                        }
                    }
                }
#pragma unroll 1
                for (int ps = 0; ps < 2; ps++) {
                const int lim = ps ? nhi : 0;
                if (ps) {
                    mma_pass<2>(ay, sb, warp, lane, true, 1, 92, 60, 16, 0, 2, 4, 0, 0);
                    mbar_wait(bar + B_G * 8, 0);
                }
#pragma unroll
                for (int i = 0; i < 36; i++) asm volatile("" : "+r"(xs[i]));
                float* op = P.out + ((T0 + 2 * q) * DM + 64 * r + 16 * warp + (lane >> 2));
#pragma unroll
                for (int jj = 0; jj < 9; jj++) {
                    uint32_t gw[4];
                    ldsm4t(img_addr(sb + SM_STGA, lrow, gq) + jj * 2048, gw[0], gw[1], gw[2], gw[3]);
#pragma unroll
                    for (int k = 0; k < 4; k++) {
                        const int j = 2 * jj + (k >> 1), i = k & 1;
                        asm volatile("{.reg .pred p; setp.lt.u32 p, %3, %4; @p st.global.f32 [%0], %1; @p st.global.f32 [%0 + 2048], %2;}"
                                     ::"l"(op + 8 * j * DM + 8 * i), "f"(fmaf(ay[4 * j + 2 * i], bf_lo(gw[k]), bf_lo(xs[2 * j + i]))),
                                       "f"(fmaf(ay[4 * j + 2 * i + 1], bf_hi(gw[k]), bf_hi(xs[2 * j + i]))), "r"(8 * j + 2 * q - 2), "r"(lim));
                    }
                }
                }
            }
        }
    }
}

typedef CUresult (*EncodeFn)(CUtensorMap*, CUtensorMapDataType, cuuint32_t, void*, const cuuint64_t*, const cuuint64_t*,
                             const cuuint32_t*, const cuuint32_t*, CUtensorMapInterleave, CUtensorMapSwizzle,
                             CUtensorMapL2promotion, CUtensorMapFloatOOBfill);

void make_map(EncodeFn fn, CUtensorMap* m, const void* p, int cols, int rows, int box_rows) {
    cuuint64_t dims[2] = {(cuuint64_t)cols, (cuuint64_t)rows};
    cuuint64_t strides[1] = {(cuuint64_t)cols * 2};
    cuuint32_t box[2] = {64, (cuuint32_t)box_rows};
    cuuint32_t es[2] = {1, 1};
    fn(m, CU_TENSOR_MAP_DATA_TYPE_BFLOAT16, 2, const_cast<void*>(p), dims, strides, box, es, CU_TENSOR_MAP_INTERLEAVE_NONE,
       CU_TENSOR_MAP_SWIZZLE_128B, CU_TENSOR_MAP_L2_PROMOTION_L2_128B, CU_TENSOR_MAP_FLOAT_OOB_FILL_NONE);
}

}

extern "C" void kernel_launch(void* const* d_in, const int* in_sizes, int n_in, void* d_out, int out_size) {
    (void)in_sizes; (void)n_in; (void)out_size;
    void* fnp = nullptr;
    cudaDriverEntryPointQueryResult qr;
    cudaGetDriverEntryPoint("cuTensorMapEncodeTiled", &fnp, cudaEnableDefault, &qr);
    EncodeFn fn = (EncodeFn)fnp;
    Params P;
    make_map(fn, &P.x, d_in[0], DM, L_SEQ, ROWS_CP);
    make_map(fn, &P.w[1], d_in[3], DM, DM, 64);
    make_map(fn, &P.w[3], d_in[4], DM, DM, 64);
    make_map(fn, &P.w[5], d_in[5], DM, DM, 64);
    make_map(fn, &P.w[7], d_in[6], DM, DM, 64);
    make_map(fn, &P.w[0], d_in[10], DM, DM, 64);
    make_map(fn, &P.w[2], d_in[11], DM, DM, 64);
    make_map(fn, &P.w[4], d_in[12], FF, DM, 64);
    make_map(fn, &P.w[6], d_in[13], DM, FF, 64);
    {
        void* img = nullptr;
        cudaGetSymbolAddress(&img, g_img);
        cuuint64_t dims[3] = {512, 18, NBLK * CL};
        cuuint64_t strides[2] = {1024, (cuuint64_t)NIMG * SLOT};
        cuuint32_t box[3] = {128, 9, CL};
        cuuint32_t es[3] = {1, 1, 1};
        fn(&P.xn, CU_TENSOR_MAP_DATA_TYPE_BFLOAT16, 3, (unsigned char*)img + 8 * SLOT, dims, strides, box, es, CU_TENSOR_MAP_INTERLEAVE_NONE,
           CU_TENSOR_MAP_SWIZZLE_NONE, CU_TENSOR_MAP_L2_PROMOTION_NONE, CU_TENSOR_MAP_FLOAT_OOB_FILL_NONE);
    }
    P.xp = (const __nv_bfloat16*)d_in[0];
    P.lre = (const __nv_bfloat16*)d_in[1];
    P.lim = (const __nv_bfloat16*)d_in[2];
    P.ldt = (const __nv_bfloat16*)d_in[7];
    P.dsk = (const __nv_bfloat16*)d_in[8];
    const int order[8] = {10, 3, 4, 11, 12, 13, 5, 6};
    for (int i = 0; i < 8; i++) P.pf[i] = (const unsigned char*)d_in[order[i]];
    P.out = (float*)d_out;
    cudaFuncSetAttribute(fused_kernel, cudaFuncAttributeMaxDynamicSharedMemorySize, SMEM_BYTES);
    fused_kernel<<<NBLK * CL, 512, SMEM_BYTES>>>(P);
}
```
